```python
import torch

def _softmax(x, axis=-1):
    return torch.softmax(x, dim=axis)

def _gelu(x):
    return torch.nn.functional.gelu(x, approximate='tanh')

def _silu(x):
    return torch.nn.functional.silu(x)

def _sigmoid(x):
    return torch.sigmoid(x)

def _layernorm(x, axis=-1, eps=1e-05):
    m = x.mean(dim=axis, keepdim=True)
    v = x.var(dim=axis, keepdim=True, unbiased=False)
    return (x - m) / torch.sqrt(v + eps)

def _scatter_add(tgt, idx, src, axis=0):
    return tgt.clone().index_add_(axis, idx, src)

def _segment_sum(src, seg, n):
    out = torch.zeros((n,) + src.shape[1:], dtype=src.dtype)
    return out.index_add_(0, seg, src)

def _pad(x, pw):
    flat = tuple((v for pair in reversed(pw) for v in pair))
    return torch.nn.functional.pad(x, flat)
kernel_name = 'standalone__tree_speculative_verify_tree_attention_over_candidate_token_tree__decode'

def setup_inputs():

    _w = lambda a: (lambda t: t.to(torch.bfloat16) if t.is_floating_point() else t)(torch.as_tensor(a))
    B, Hq, Hkv, T, C, D = (2, 32, 16, 1, 8192, 128)
    tree_mask = torch.zeros((B, T, T), dtype=float)
    for b in range(B):
        parent = torch.zeros(T, dtype=torch.int64)
        for i in range(1, T):
            parent[i] = int(torch.randint(0, i, (1,)).item())
        for i in range(T):
            j = i
            tree_mask[b, i, j] = 1.0
            while j > 0:
                j = parent[j]
                tree_mask[b, i, j] = 1.0
    return {'q': _w((lambda *s: torch.randn(*s, dtype=torch.bfloat16) * 0.8)(B, Hq, T, D)), 'k_cache': _w((lambda *s: torch.randn(*s, dtype=torch.bfloat16) * 0.8)(B, Hkv, C, D)), 'v_cache': _w((lambda *s: torch.randn(*s, dtype=torch.bfloat16) * 0.05)(B, Hkv, C, D)), 'k_tree': _w((lambda *s: torch.randn(*s, dtype=torch.bfloat16) * 0.8)(B, Hkv, T, D)), 'v_tree': _w((lambda *s: torch.randn(*s, dtype=torch.bfloat16) * 0.05)(B, Hkv, T, D)), 'tree_mask': _w(tree_mask)}

def reference(q, k_cache, v_cache, k_tree, v_tree, tree_mask):
    B, Hq, T, D = q.shape
    Hkv, C = (k_cache.shape[1], k_cache.shape[2])
    rep = Hq // Hkv
    kc = (lambda x, n, axis: torch.repeat_interleave(x, n, dim=axis))(k_cache, rep, axis=1)
    vc = (lambda x, n, axis: torch.repeat_interleave(x, n, dim=axis))(v_cache, rep, axis=1)
    kt = (lambda x, n, axis: torch.repeat_interleave(x, n, dim=axis))(k_tree, rep, axis=1)
    vt = (lambda x, n, axis: torch.repeat_interleave(x, n, dim=axis))(v_tree, rep, axis=1)
    k = torch.concatenate([kc, kt], axis=2)
    v = torch.concatenate([vc, vt], axis=2)
    scale = D ** (-0.5)
    scores = torch.einsum('bhqd,bhkd->bhqk', q, k) * scale
    ctx_mask = torch.ones((B, 1, T, C), dtype=scores.dtype)
    tm = tree_mask[:, None, :, :].clone()
    full_mask = torch.concatenate([ctx_mask, tm], axis=-1)
    scores = scores + (1.0 - full_mask) * -1000000000.0
    p = _softmax(scores, axis=-1)
    return torch.einsum('bhqk,bhkd->bhqd', p, v)
```

```cpp
#include <cuda_runtime.h>
#include <cuda_bf16.h>
#include <cuda.h>
#include <stdint.h>

namespace ta {

constexpr int NB = 2, HQ = 32, HKV = 16, CTX = 8192, HD = 128;
constexpr int NHEAD = NB * HKV;
constexpr int NSPLIT = 4;
constexpr int KEYS = CTX / NSPLIT;
constexpr int NCW = 8;
constexpr int NTHREADS = (NCW + 2) * 32;
constexpr float LOG2E = 1.4426950408889634f;
constexpr float SCALE = 0.08838834764831845f;
constexpr uint32_t SPIN_LIMIT = 1u << 24;

__device__ unsigned long long g_part[NHEAD][NSPLIT - 1][NCW * 32];
__device__ unsigned long long g_ml[NHEAD][NSPLIT - 1][4];
__device__ unsigned int g_epoch[NHEAD];

__device__ __forceinline__ uint32_t smem_u32(const void* p) { return (uint32_t)__cvta_generic_to_shared(p); }
__device__ __forceinline__ void mbar_init(uint32_t bar, uint32_t cnt) {
    asm volatile("mbarrier.init.shared::cta.b64 [%0], %1;" ::"r"(bar), "r"(cnt) : "memory");
}
__device__ __forceinline__ void mbar_expect_tx(uint32_t bar, uint32_t bytes) {
    asm volatile("mbarrier.arrive.expect_tx.shared::cta.b64 _, [%0], %1;" ::"r"(bar), "r"(bytes) : "memory");
}
__device__ __forceinline__ void mbar_arrive(uint32_t bar) {
    asm volatile("mbarrier.arrive.shared::cta.b64 _, [%0];" ::"r"(bar) : "memory");
}
__device__ __forceinline__ void mbar_wait(uint32_t bar, uint32_t parity) {
    uint32_t ok, it = 0;
    do {
        asm volatile("{\n\t.reg .pred p;\n\tmbarrier.try_wait.parity.shared::cta.b64 p, [%1], %2;\n\tselp.u32 %0, 1, 0, p;\n\t}"
                     : "=r"(ok) : "r"(bar), "r"(parity) : "memory");
        if (++it > SPIN_LIMIT) __trap();
    } while (!ok);
}
__device__ __forceinline__ void named_sync(int id, int n) { asm volatile("bar.sync %0, %1;" ::"r"(id), "r"(n) : "memory"); }
__device__ __forceinline__ void ldsm4(uint32_t (&r)[4], uint32_t a) {
    asm volatile("ldmatrix.sync.aligned.m8n8.x4.shared.b16 {%0,%1,%2,%3}, [%4];"
                 : "=r"(r[0]), "=r"(r[1]), "=r"(r[2]), "=r"(r[3]) : "r"(a) : "memory");
}
__device__ __forceinline__ void ldsm4t(uint32_t (&r)[4], uint32_t a) {
    asm volatile("ldmatrix.sync.aligned.m8n8.x4.trans.shared.b16 {%0,%1,%2,%3}, [%4];"
                 : "=r"(r[0]), "=r"(r[1]), "=r"(r[2]), "=r"(r[3]) : "r"(a) : "memory");
}
__device__ __forceinline__ void mma16816(float (&c)[4], const uint32_t (&a)[4], uint32_t b0, uint32_t b1) {
    asm volatile("mma.sync.aligned.m16n8k16.row.col.f32.bf16.bf16.f32 {%0,%1,%2,%3}, {%4,%5,%6,%7}, {%8,%9}, {%0,%1,%2,%3};"
                 : "+f"(c[0]), "+f"(c[1]), "+f"(c[2]), "+f"(c[3])
                 : "r"(a[0]), "r"(a[1]), "r"(a[2]), "r"(a[3]), "r"(b0), "r"(b1));
}
__device__ __forceinline__ unsigned long long ld_relaxed(const unsigned long long* p) {
    unsigned long long v;
    asm volatile("ld.relaxed.gpu.global.b64 %0, [%1];" : "=l"(v) : "l"(p) : "memory");
    return v;
}
__device__ __forceinline__ void st_relaxed(unsigned long long* p, float x, uint32_t tag) {
    unsigned long long v = ((unsigned long long)tag << 32) | __float_as_uint(x);
    asm volatile("st.relaxed.gpu.global.b64 [%0], %1;" ::"l"(p), "l"(v) : "memory");
}
__device__ __forceinline__ float bf16r(float x) { return __bfloat162float(__float2bfloat16_rn(x)); }
__device__ __forceinline__ float bf_lo(uint32_t x) { return __uint_as_float(x << 16); }
__device__ __forceinline__ float bf_hi(uint32_t x) { return __uint_as_float(x & 0xffff0000u); }
__device__ __forceinline__ uint32_t pack_bf16(float lo, float hi) {
    uint32_t r;
    asm("cvt.rn.bf16x2.f32 %0, %1, %2;" : "=r"(r) : "f"(hi), "f"(lo));
    return r;
}
__device__ __forceinline__ float ex2(float x) {
    float r;
    asm("ex2.approx.ftz.f32 %0, %1;" : "=f"(r) : "f"(x));
    return r;
}

struct __align__(16) Misc {
    float wgt[2][8];
    float mred[NCW][2];
    float lred[NCW][2];
    unsigned long long full[16];
    unsigned long long empty[16];
    unsigned long long wready;
    uint32_t tag;
};

template <int TILE, int STAGES, int INFLIGHT, int INTER, int HINT>
__global__ void __launch_bounds__(NTHREADS, 1)
tree_attn_kernel(const __grid_constant__ CUtensorMap map_k, const __grid_constant__ CUtensorMap map_v,
                 const __nv_bfloat16* __restrict__ q, const __nv_bfloat16* __restrict__ k_tree,
                 const __nv_bfloat16* __restrict__ v_tree, const __nv_bfloat16* __restrict__ tree_mask,
                 __nv_bfloat16* __restrict__ out) {
    constexpr int NT = KEYS / TILE;
    constexpr int TB = TILE * HD * 2;
    constexpr int HALF = TILE * 128;
    constexpr int KG = TILE / 16;
    extern __shared__ unsigned char smem_raw[];
    __shared__ Misc misc;
    __shared__ __align__(128) unsigned char pbuf[KEYS * 2 * 2];

    const int tid = threadIdx.x, warp = tid >> 5, lane = tid & 31;
    const int bh = blockIdx.x / NSPLIT, split = blockIdx.x % NSPLIT;
    const uint32_t ring = (smem_u32(smem_raw) + 1023u) & ~1023u;
    const uint32_t full0 = smem_u32(&misc.full[0]), empty0 = smem_u32(&misc.empty[0]);

    if (warp == NCW) {
        uint64_t pol = 0;
        if (HINT) asm volatile("createpolicy.fractional.L2::evict_first.b64 %0, 1.0;" : "=l"(pol));
        auto issue = [&](int i, int s) {
            const int t = i < NT ? i : i - NT;
            const int row = bh * CTX + (INTER ? (t * NSPLIT + split) : (split * NT + t)) * TILE;
            const CUtensorMap* m = i < NT ? &map_k : &map_v;
            mbar_expect_tx(full0 + 8 * s, TB);
            if (HINT)
                asm volatile("cp.async.bulk.tensor.3d.shared::cluster.global.mbarrier::complete_tx::bytes.L2::cache_hint [%0], [%1, {%3, %4, %3}], [%2], %5;"
                             ::"r"(ring + s * TB), "l"(m), "r"(full0 + 8 * s), "r"(0), "r"(row), "l"(pol) : "memory");
            else
                asm volatile("cp.async.bulk.tensor.3d.shared::cluster.global.mbarrier::complete_tx::bytes [%0], [%1, {%3, %4, %3}], [%2];"
                             ::"r"(ring + s * TB), "l"(m), "r"(full0 + 8 * s), "r"(0), "r"(row) : "memory");
        };
        if (lane == 0) {
#pragma unroll
            for (int s = 0; s < STAGES; s++) mbar_init(full0 + 8 * s, 1);
            asm volatile("fence.mbarrier_init.release.cluster;" ::: "memory");
#pragma unroll
            for (int i = 0; i < INFLIGHT; i++) issue(i, i);
#pragma unroll
            for (int s = 0; s < STAGES; s++) mbar_init(empty0 + 8 * s, NCW);
            mbar_init(smem_u32(&misc.wready), 1);
        }
        __syncthreads();
        if (lane == 0) {
            int s = INFLIGHT % STAGES, ph = (INFLIGHT / STAGES) & 1;
            int sf = 0, phf = 0;
#pragma unroll 1
            for (int i = INFLIGHT; i < 2 * NT; i++) {
                if (INFLIGHT < STAGES) {
                    mbar_wait(full0 + 8 * sf, phf);
                    if (++sf == STAGES) { sf = 0; phf ^= 1; }
                }
                if (i >= STAGES) mbar_wait(empty0 + 8 * s, ph ^ 1);
                issue(i, s);
                if (++s == STAGES) { s = 0; ph ^= 1; }
            }
        }
    } else if (warp == NCW + 1) {
        uint32_t tag = 0;
        float st[2] = {0.f, 0.f};
        if (lane == 0) {
            asm volatile("ld.relaxed.gpu.global.u32 %0, [%1];" : "=r"(tag) : "l"(&g_epoch[bh]) : "memory");
            tag += 1;
            misc.tag = tag;
        }
        tag = __shfl_sync(0xffffffffu, tag, 0);
        if (split == 0) {
            const uint2 kt = *reinterpret_cast<const uint2*>(k_tree + bh * HD + lane * 4);
            const float mk = __bfloat162float(tree_mask[bh / HKV]);
            const float madd = bf16r(bf16r(1.0f - mk) * -1000000000.0f);
#pragma unroll
            for (int h = 0; h < 2; h++) {
                const uint2 qv = *reinterpret_cast<const uint2*>(q + (2 * bh + h) * HD + lane * 4);
                float a = bf_lo(qv.x) * bf_lo(kt.x) + bf_hi(qv.x) * bf_hi(kt.x) + bf_lo(qv.y) * bf_lo(kt.y) + bf_hi(qv.y) * bf_hi(kt.y);
#pragma unroll
                for (int o = 16; o > 0; o >>= 1) a += __shfl_xor_sync(0xffffffffu, a, o);
                st[h] = bf16r(bf16r(bf16r(a) * SCALE) + madd);
            }
        }
        __syncthreads();
        named_sync(2, (NCW + 1) * 32);
        const int h = lane & 1;
        float m = misc.mred[0][h], l = misc.lred[0][h];
#pragma unroll
        for (int w = 1; w < NCW; w++) { m = fmaxf(m, misc.mred[w][h]); l += misc.lred[w][h]; }
        if (split != 0) {
            if (lane < 4) st_relaxed(&g_ml[bh][split - 1][lane], (lane & 2) ? l : m, tag);
        } else {
            float x = (lane & 2) ? l : m;
            if (lane >= 4 && lane < 16) {
                const unsigned long long* p = &g_ml[bh][(lane >> 2) - 1][lane & 3];
                unsigned long long v = ld_relaxed(p);
                uint32_t it = 0;
                while ((uint32_t)(v >> 32) != tag) {
                    __nanosleep(200);
                    v = ld_relaxed(p);
                    if (++it > SPIN_LIMIT) __trap();
                }
                x = __uint_as_float((uint32_t)v);
            }
            __syncwarp();
            float mi[4], li[4];
#pragma unroll
            for (int i = 0; i < 4; i++) {
                mi[i] = __shfl_sync(0xffffffffu, x, 4 * i + h);
                li[i] = __shfl_sync(0xffffffffu, x, 4 * i + 2 + h);
            }
            const float s_t = h ? st[1] : st[0];
            const float M = fmaxf(fmaxf(fmaxf(mi[0], mi[1]), fmaxf(mi[2], mi[3])), s_t);
            float e[5], L;
            e[4] = ex2((s_t - M) * LOG2E);
            L = e[4];
#pragma unroll
            for (int i = 0; i < 4; i++) { e[i] = ex2((mi[i] - M) * LOG2E); L += e[i] * li[i]; }
            const float inv = 1.0f / L;
            if (lane < 2) {
#pragma unroll
                for (int i = 0; i < 5; i++) misc.wgt[h][i] = e[i] * inv;
            }
            __syncwarp();
            if (lane == 0) mbar_arrive(smem_u32(&misc.wready));
        }
    } else {
        const int g = lane >> 2, t = lane & 3;
        uint32_t qf[8][2];
        {
            const uint32_t* qp = reinterpret_cast<const uint32_t*>(q + (2 * bh + (g & 1)) * HD) + t;
#pragma unroll
            for (int j = 0; j < 8; j++) { qf[j][0] = __ldg(qp + 8 * j); qf[j][1] = __ldg(qp + 8 * j + 4); }
        }
        const int oh = t & 1, od = 16 * warp + g + 8 * (t >> 1);
        float vt = 0.f;
        if (split == 0) vt = __bfloat162float(v_tree[bh * HD + od]);
        __syncthreads();

        int s = 0, ph = 0;
        const int kgw = warp % KG;
        const uint32_t pb = smem_u32(pbuf);
        float mx = -INFINITY;
        {
            const uint32_t roff = (16 * kgw + (lane & 7) + 8 * ((lane >> 3) & 1)) * 128;
            const uint32_t x = (lane >> 4) ^ (lane & 7);
            const uint32_t soff = oh * 64 + (g >> 1) * 16 + (2 * (t >> 1) + (g & 1)) * 2;
#pragma unroll 1
            for (int i = 0; i < NT; i++) {
                mbar_wait(full0 + 8 * s, ph);
                if (KG == NCW || (warp / KG) == (i % (NCW / KG))) {
                    const uint32_t base = ring + s * TB + roff;
                    float c0[4] = {0.f, 0.f, 0.f, 0.f}, c1[4] = {0.f, 0.f, 0.f, 0.f};
                    uint32_t a[8][4];
#pragma unroll
                    for (int j = 0; j < 8; j++) ldsm4(a[j], base + (j >> 2) * HALF + (((2 * (j & 3)) ^ x) << 4));
#pragma unroll
                    for (int j = 0; j < 8; j += 2) {
                        mma16816(c0, a[j], qf[j][0], qf[j][1]);
                        mma16816(c1, a[j + 1], qf[j + 1][0], qf[j + 1][1]);
                    }
                    __syncwarp();
                    if (lane == 0) mbar_arrive(empty0 + 8 * s);
                    const float lo = (t & 1) ? c0[1] + c1[1] : c0[0] + c1[0];
                    const float hi = (t & 1) ? c0[3] + c1[3] : c0[2] + c1[2];
                    const __nv_bfloat16 sb = __float2bfloat16_rn(bf16r((t & 2) ? hi : lo) * SCALE);
                    mx = fmaxf(mx, __bfloat162float(sb));
                    const int gi = i * KG + kgw;
                    asm volatile("st.shared.b16 [%0], %1;" ::"r"(pb + (gi >> 1) * 128 + (gi & 1) * 8 + soff), "h"(__bfloat16_as_ushort(sb)) : "memory");
                } else {
                    __syncwarp();
                    if (lane == 0) mbar_arrive(empty0 + 8 * s);
                }
                if (++s == STAGES) { s = 0; ph ^= 1; }
            }
        }
#pragma unroll
        for (int o = 2; o < 32; o <<= 1) mx = fmaxf(mx, __shfl_xor_sync(0xffffffffu, mx, o));
        if (lane < 2) misc.mred[warp][lane] = mx;
        named_sync(1, NCW * 32);
        {
            const int h = (tid >> 2) & 1;
            float m = misc.mred[0][h];
#pragma unroll
            for (int w = 1; w < NCW; w++) m = fmaxf(m, misc.mred[w][h]);
            float l = 0.f;
#pragma unroll
            for (int r = 0; r < KEYS * 4 / 16 / (NCW * 32); r++) {
                uint4* pp = reinterpret_cast<uint4*>(pbuf) + tid + r * NCW * 32;
                uint4 v = *pp;
                uint32_t* u = reinterpret_cast<uint32_t*>(&v);
#pragma unroll
                for (int e = 0; e < 4; e++) {
                    const float p0 = ex2((bf_lo(u[e]) - m) * LOG2E), p1 = ex2((bf_hi(u[e]) - m) * LOG2E);
                    l += p0 + p1;
                    u[e] = pack_bf16(p0, p1);
                }
                *pp = v;
            }
            l += __shfl_xor_sync(0xffffffffu, l, 1);
            l += __shfl_xor_sync(0xffffffffu, l, 2);
            l += __shfl_xor_sync(0xffffffffu, l, 8);
            l += __shfl_xor_sync(0xffffffffu, l, 16);
            if ((lane & ~4) == 0) misc.lred[warp][lane >> 2] = l;
        }
        named_sync(2, (NCW + 1) * 32);
        const uint32_t tag = misc.tag;

        float o0[4] = {0.f, 0.f, 0.f, 0.f}, o1[4] = {0.f, 0.f, 0.f, 0.f};
        const uint32_t voff = (warp >> 2) * HALF + ((lane & 7) + 8 * (lane >> 4)) * 128 +
                              ((((2 * warp + ((lane >> 3) & 1)) & 7) ^ (lane & 7)) << 4);
        const uint32_t poff = pb + (g & 1) * 64 + t * 16;
        auto pv_tile = [&](int i) {
            uint4 pf[KG / 2];
#pragma unroll
            for (int kp = 0; kp < KG / 2; kp++)
                asm volatile("ld.shared.v4.u32 {%0,%1,%2,%3}, [%4];" : "=r"(pf[kp].x), "=r"(pf[kp].y), "=r"(pf[kp].z), "=r"(pf[kp].w)
                             : "r"(poff + (i * (KG / 2) + kp) * 128));
            mbar_wait(full0 + 8 * s, ph);
            const uint32_t base = ring + s * TB + voff;
            uint32_t a[KG][4];
#pragma unroll
            for (int kg = 0; kg < KG; kg++) ldsm4t(a[kg], base + kg * 2048);
#pragma unroll
            for (int kp = 0; kp < KG / 2; kp++) {
                mma16816(o0, a[2 * kp], pf[kp].x, pf[kp].y);
                mma16816(o1, a[2 * kp + 1], pf[kp].z, pf[kp].w);
            }
        };
#pragma unroll 1
        for (int i = 0; i < NT - 1; i++) {
            pv_tile(i);
            __syncwarp();
            if (lane == 0) mbar_arrive(empty0 + 8 * s);
            if (++s == STAGES) { s = 0; ph ^= 1; }
        }
        if (split != 0) {
            pv_tile(NT - 1);
            const float lo = (t & 1) ? o0[1] + o1[1] : o0[0] + o1[0];
            const float hi = (t & 1) ? o0[3] + o1[3] : o0[2] + o1[2];
            st_relaxed(&g_part[bh][split - 1][tid], (t & 2) ? hi : lo, tag);
        } else {
            mbar_wait(smem_u32(&misc.wready), 0);
            const float4 w = *reinterpret_cast<const float4*>(&misc.wgt[oh][0]);
            const float acc_t = misc.wgt[oh][4] * vt;
            const unsigned long long* pp = &g_part[bh][0][tid];
            unsigned long long r0 = ld_relaxed(pp), r1 = ld_relaxed(pp + NCW * 32), r2 = ld_relaxed(pp + 2 * NCW * 32);
            pv_tile(NT - 1);
            const float lo = (t & 1) ? o0[1] + o1[1] : o0[0] + o1[0];
            const float hi = (t & 1) ? o0[3] + o1[3] : o0[2] + o1[2];
            const float own = fmaf(w.x, (t & 2) ? hi : lo, acc_t);
            uint32_t it = 0;
            while ((uint32_t)(r0 >> 32) != tag || (uint32_t)(r1 >> 32) != tag || (uint32_t)(r2 >> 32) != tag) {
                if ((uint32_t)(r0 >> 32) != tag) r0 = ld_relaxed(pp);
                if ((uint32_t)(r1 >> 32) != tag) r1 = ld_relaxed(pp + NCW * 32);
                if ((uint32_t)(r2 >> 32) != tag) r2 = ld_relaxed(pp + 2 * NCW * 32);
                if (++it > SPIN_LIMIT) __trap();
            }
            const float r = fmaf(w.w, __uint_as_float((uint32_t)r2),
                            fmaf(w.z, __uint_as_float((uint32_t)r1), fmaf(w.y, __uint_as_float((uint32_t)r0), own)));
            out[(2 * bh + oh) * HD + od] = __float2bfloat16_rn(r);
            if (tid == 0) g_epoch[bh] = tag;
        }
    }
}

typedef CUresult (*EncodeFn)(CUtensorMap*, CUtensorMapDataType, cuuint32_t, void*, const cuuint64_t*, const cuuint64_t*,
                             const cuuint32_t*, const cuuint32_t*, CUtensorMapInterleave, CUtensorMapSwizzle,
                             CUtensorMapL2promotion, CUtensorMapFloatOOBfill);

static void make_map(CUtensorMap* m, const void* base, int tile, int promo) {
    static EncodeFn enc = nullptr;
    if (!enc) {
        cudaDriverEntryPointQueryResult qr;
        cudaGetDriverEntryPoint("cuTensorMapEncodeTiled", (void**)&enc, cudaEnableDefault, &qr);
    }
    cuuint64_t gd[3] = {64, (cuuint64_t)NHEAD * CTX, 2};
    cuuint64_t gs[2] = {256, 128};
    cuuint32_t bd[3] = {64, (cuuint32_t)tile, 2};
    cuuint32_t es[3] = {1, 1, 1};
    enc(m, CU_TENSOR_MAP_DATA_TYPE_BFLOAT16, 3, const_cast<void*>(base), gd, gs, bd, es, CU_TENSOR_MAP_INTERLEAVE_NONE,
        CU_TENSOR_MAP_SWIZZLE_128B, (CUtensorMapL2promotion)promo, CU_TENSOR_MAP_FLOAT_OOB_FILL_NONE);
}

template <int TILE, int STAGES, int INFLIGHT, int INTER, int HINT>
static void launch(void* const* d_in, void* d_out, int promo, cudaStream_t stream) {
    auto kern = tree_attn_kernel<TILE, STAGES, INFLIGHT, INTER, HINT>;
    constexpr int smem = STAGES * TILE * HD * 2 + 1024;
    cudaFuncSetAttribute(kern, cudaFuncAttributeMaxDynamicSharedMemorySize, smem);
    CUtensorMap mk, mv;
    make_map(&mk, d_in[1], TILE, promo);
    make_map(&mv, d_in[2], TILE, promo);
    kern<<<NHEAD * NSPLIT, NTHREADS, smem, stream>>>(mk, mv, (const __nv_bfloat16*)d_in[0], (const __nv_bfloat16*)d_in[3],
                                                     (const __nv_bfloat16*)d_in[4], (const __nv_bfloat16*)d_in[5],
                                                     (__nv_bfloat16*)d_out);
}

}

extern "C" void kernel_launch(void* const* d_in, const int* in_sizes, int n_in, void* d_out, int out_size) {
    (void)in_sizes; (void)n_in; (void)out_size;
    ta::launch<128, 5, 4, 0, 1>(d_in, d_out, 3, cudaStreamPerThread);
}
```

```cpp
#include <cuda_runtime.h>
#include <cuda_bf16.h>
#include <cuda.h>
#include <stdint.h>

namespace ta {

constexpr int NB = 2, HKV = 16, CTX = 8192, HD = 128;
constexpr int NHEAD = NB * HKV;
constexpr int NSPLIT = 4;
constexpr int KEYS = CTX / NSPLIT;
constexpr int NCW = 8;
constexpr int NTHREADS = (NCW + 2) * 32;
constexpr float LOG2E = 1.4426950408889634f;
constexpr float SCALE = 0.08838834764831845f;
constexpr uint32_t SPIN_LIMIT = 1u << 24;
constexpr uint64_t EVICT_FIRST = 0x12F0000000000000ull;

__device__ unsigned long long g_part[NHEAD][NSPLIT - 1][NCW * 32];
__device__ unsigned long long g_ml[NHEAD][NSPLIT - 1][4];
__device__ unsigned long long g_ml2[NHEAD][NSPLIT][NSPLIT][4];

#define TSTAMP(i) do {} while (0)

__device__ __forceinline__ uint32_t smem_u32(const void* p) { return (uint32_t)__cvta_generic_to_shared(p); }
__device__ __forceinline__ void mbar_init(uint32_t bar, uint32_t cnt) {
    asm volatile("mbarrier.init.shared::cta.b64 [%0], %1;" ::"r"(bar), "r"(cnt) : "memory");
}
__device__ __forceinline__ void mbar_expect_tx(uint32_t bar, uint32_t bytes) {
    asm volatile("mbarrier.arrive.expect_tx.shared::cta.b64 _, [%0], %1;" ::"r"(bar), "r"(bytes) : "memory");
}
__device__ __forceinline__ void mbar_arrive(uint32_t bar) {
    asm volatile("mbarrier.arrive.shared::cta.b64 _, [%0];" ::"r"(bar) : "memory");
}
__device__ __forceinline__ void mbar_wait(uint32_t bar, uint32_t parity) {
    uint32_t ok, it = 0;
    do {
        asm volatile("{\n\t.reg .pred p;\n\tmbarrier.try_wait.parity.shared::cta.b64 p, [%1], %2;\n\tselp.u32 %0, 1, 0, p;\n\t}"
                     : "=r"(ok) : "r"(bar), "r"(parity) : "memory");
        if (++it > SPIN_LIMIT) __trap();
    } while (!ok);
}
__device__ __forceinline__ void named_sync(int id, int n) { asm volatile("bar.sync %0, %1;" ::"r"(id), "r"(n) : "memory"); }
__device__ __forceinline__ void ldsm4(uint32_t (&r)[4], uint32_t a) {
    asm volatile("ldmatrix.sync.aligned.m8n8.x4.shared.b16 {%0,%1,%2,%3}, [%4];"
                 : "=r"(r[0]), "=r"(r[1]), "=r"(r[2]), "=r"(r[3]) : "r"(a) : "memory");
}
__device__ __forceinline__ void ldsm4t(uint32_t (&r)[4], uint32_t a) {
    asm volatile("ldmatrix.sync.aligned.m8n8.x4.trans.shared.b16 {%0,%1,%2,%3}, [%4];"
                 : "=r"(r[0]), "=r"(r[1]), "=r"(r[2]), "=r"(r[3]) : "r"(a) : "memory");
}
__device__ __forceinline__ void mma16816(float (&c)[4], const uint32_t (&a)[4], uint32_t b0, uint32_t b1) {
    asm volatile("mma.sync.aligned.m16n8k16.row.col.f32.bf16.bf16.f32 {%0,%1,%2,%3}, {%4,%5,%6,%7}, {%8,%9}, {%0,%1,%2,%3};"
                 : "+f"(c[0]), "+f"(c[1]), "+f"(c[2]), "+f"(c[3])
                 : "r"(a[0]), "r"(a[1]), "r"(a[2]), "r"(a[3]), "r"(b0), "r"(b1));
}
__device__ __forceinline__ unsigned long long ld_relaxed(const unsigned long long* p) {
    unsigned long long v;
    asm volatile("ld.relaxed.gpu.global.b64 %0, [%1];" : "=l"(v) : "l"(p) : "memory");
    return v;
}
__device__ __forceinline__ void st_relaxed(unsigned long long* p, float x, uint32_t tag) {
    unsigned long long v = ((unsigned long long)tag << 32) | __float_as_uint(x);
    asm volatile("st.relaxed.gpu.global.b64 [%0], %1;" ::"l"(p), "l"(v) : "memory");
}
__device__ __forceinline__ float bf16r(float x) { return __bfloat162float(__float2bfloat16_rn(x)); }
__device__ __forceinline__ float bf_lo(uint32_t x) { return __uint_as_float(x << 16); }
__device__ __forceinline__ float bf_hi(uint32_t x) { return __uint_as_float(x & 0xffff0000u); }
__device__ __forceinline__ uint32_t pack_bf16(float lo, float hi) {
    uint32_t r;
    asm("cvt.rn.bf16x2.f32 %0, %1, %2;" : "=r"(r) : "f"(hi), "f"(lo));
    return r;
}
__device__ __forceinline__ float ex2(float x) {
    float r;
    asm("ex2.approx.ftz.f32 %0, %1;" : "=f"(r) : "f"(x));
    return r;
}

struct __align__(16) Misc {
    float wgt[2][8];
    float mred[NCW][2];
    float lred[NCW][2];
    unsigned long long full[8];
    unsigned long long tail[8];
    unsigned long long empty[8];
    unsigned long long wready;
};

__device__ __forceinline__ bool elect_one() {
    uint32_t p;
    asm volatile("{\n\t.reg .pred p;\n\telect.sync _|p, 0xffffffff;\n\tselp.u32 %0, 1, 0, p;\n\t}" : "=r"(p));
    return p != 0;
}

template <int TILE, int STAGES>
constexpr int smem_bytes() { return STAGES * TILE * HD * 2 + KEYS * 4 + (int)sizeof(Misc); }

template <int TILE, int STAGES, int INFLIGHT, int SUB, int HINT, int XMODE = 0>
__global__ void __launch_bounds__(NTHREADS, 1)
tree_attn_kernel(const __grid_constant__ CUtensorMap map_k, const __grid_constant__ CUtensorMap map_v,
                 const __grid_constant__ CUtensorMap map_vt,
                 const __nv_bfloat16* __restrict__ q, const __nv_bfloat16* __restrict__ k_tree,
                 const __nv_bfloat16* __restrict__ v_tree, const __nv_bfloat16* __restrict__ tree_mask,
                 __nv_bfloat16* __restrict__ out) {
    constexpr int NT = KEYS / TILE;
    constexpr int TB = TILE * HD * 2;
    constexpr int SR = TILE / SUB;
    constexpr int SB = TB / SUB;
    constexpr int KG = TILE / 16;
    constexpr int SKG = SR / 16;
    extern __shared__ __align__(1024) unsigned char smem[];
    unsigned char* pbuf = smem + STAGES * TB;
    Misc& misc = *reinterpret_cast<Misc*>(smem + STAGES * TB + KEYS * 4);

    const int bh = blockIdx.x / NSPLIT, split = blockIdx.x % NSPLIT;
    const uint32_t ring = smem_u32(smem);
    const uint32_t full0 = smem_u32(&misc.full[0]), empty0 = smem_u32(&misc.empty[0]);
    const int row0 = blockIdx.x * (KEYS / 8);
    constexpr int RSTEP = TILE / 8;

    const uint32_t tail0 = smem_u32(&misc.tail[0]);
    auto tma = [&](const CUtensorMap* m, int row, uint32_t dst, uint32_t bar, uint32_t bytes) {
        mbar_expect_tx(bar, bytes);
        if (HINT)
            asm volatile("cp.async.bulk.tensor.4d.shared::cluster.global.mbarrier::complete_tx::bytes.L2::cache_hint [%0], [%1, {%3, %3, %3, %4}], [%2], %5;"
                         ::"r"(dst), "l"(m), "r"(bar), "r"(0), "r"(row), "l"(EVICT_FIRST) : "memory");
        else
            asm volatile("cp.async.bulk.tensor.4d.shared::cluster.global.mbarrier::complete_tx::bytes [%0], [%1, {%3, %3, %3, %4}], [%2];"
                         ::"r"(dst), "l"(m), "r"(bar), "r"(0), "r"(row) : "memory");
    };
    auto issue = [&](const CUtensorMap* m, int row, int s) { tma(m, row, ring + s * TB, full0 + 8 * s, TB); };

    if (threadIdx.x < 32) {
        if (elect_one()) {
            TSTAMP(0);
#pragma unroll
            for (int s = 0; s < STAGES; s++) mbar_init(full0 + 8 * s, 1);
            asm volatile("fence.mbarrier_init.release.cluster;" ::: "memory");
#pragma unroll
            for (int i = 0; i < INFLIGHT; i++) issue(&map_k, row0 + i * RSTEP, i);
            TSTAMP(1);
#pragma unroll
            for (int s = 0; s < STAGES; s++) mbar_init(empty0 + 8 * s, NCW);
            mbar_init(smem_u32(&misc.wready), 1);
#pragma unroll
            for (int j = 0; j < SUB; j++) mbar_init(tail0 + 8 * j, 1);
            asm volatile("fence.mbarrier_init.release.cluster;" ::: "memory");
            asm volatile("prefetch.tensormap [%0];" ::"l"(&map_v) : "memory");
            if (SUB > 1) asm volatile("prefetch.tensormap [%0];" ::"l"(&map_vt) : "memory");
        }
        __syncwarp();
    }

    const int lane = threadIdx.x & 31;
    const int warp = (threadIdx.x >> 5) - 2;
    if (warp == -2) {
        __syncthreads();
        if (elect_one()) {
            int s = INFLIGHT % STAGES, ph = (INFLIGHT / STAGES) & 1;
            int sf = 0, phf = 0;
#pragma unroll 1
            for (int i = INFLIGHT; i < 2 * NT; i++) {
                if (INFLIGHT < STAGES) {
                    mbar_wait(full0 + 8 * sf, phf);
                    if (++sf == STAGES) { sf = 0; phf ^= 1; }
                }
                if (i >= STAGES) mbar_wait(empty0 + 8 * s, ph ^ 1);
                if ((XMODE & 64) && SUB > 1 && i == 2 * NT - 4) asm volatile("prefetch.tensormap [%0];" ::"l"(&map_vt) : "memory");
                if ((XMODE & 64) && i == NT - 3) asm volatile("prefetch.tensormap [%0];" ::"l"(&map_v) : "memory");
                if (i < 2 * NT - 1) {
                    issue(i < NT ? &map_k : &map_v, row0 + (i % NT) * RSTEP, s);
                } else {
#pragma unroll
                    for (int j = 0; j < SUB; j++)
                        tma(SUB > 1 ? &map_vt : &map_v, row0 + (NT - 1) * RSTEP + j * (SR / 8), ring + s * TB + j * SB, tail0 + 8 * j, SB);
                }
                if (++s == STAGES) { s = 0; ph ^= 1; }
            }
        }
    } else if (warp == -1) {
        float st[2] = {0.f, 0.f};
        if (split == 0 || (XMODE & 8)) {
            const uint2 kt = *reinterpret_cast<const uint2*>(k_tree + bh * HD + lane * 4);
            const float mk = __bfloat162float(tree_mask[bh / HKV]);
            const float madd = bf16r(bf16r(1.0f - mk) * -1000000000.0f);
#pragma unroll
            for (int h = 0; h < 2; h++) {
                const uint2 qv = *reinterpret_cast<const uint2*>(q + (2 * bh + h) * HD + lane * 4);
                float a = bf_lo(qv.x) * bf_lo(kt.x) + bf_hi(qv.x) * bf_hi(kt.x) + bf_lo(qv.y) * bf_lo(kt.y) + bf_hi(qv.y) * bf_hi(kt.y);
#pragma unroll
                for (int o = 16; o > 0; o >>= 1) a += __shfl_xor_sync(0xffffffffu, a, o);
                st[h] = bf16r(bf16r(bf16r(a) * SCALE) + madd);
            }
        }
        __syncthreads();
        named_sync(2, (NCW + 1) * 32);
        const int h = lane & 1;
        float m = misc.mred[0][h], l = misc.lred[0][h];
#pragma unroll
        for (int w = 1; w < NCW; w++) { m = fmaxf(m, misc.mred[w][h]); l += misc.lred[w][h]; }
        if (XMODE & 8) {
            asm volatile("fence.acq_rel.gpu;" ::: "memory");
            if (lane < 16 && (lane >> 2) != split) st_relaxed(&g_ml2[bh][lane >> 2][split][lane & 3], (lane & 2) ? l : m, 1);
        }
        if (split != 0 && !(XMODE & 8)) {
            asm volatile("fence.acq_rel.gpu;" ::: "memory");
            if (lane < 4) st_relaxed(&g_ml[bh][split - 1][lane], (lane & 2) ? l : m, 1);
        } else {
            float x = (lane & 2) ? l : m;
            if ((lane >> 2) != split && lane < 16) {
                unsigned long long* p = (XMODE & 8) ? &g_ml2[bh][split][lane >> 2][lane & 3] : &g_ml[bh][(lane >> 2) - 1][lane & 3];
                unsigned long long v = ld_relaxed(p);
                uint32_t it = 0;
                while ((uint32_t)(v >> 32) == 0) {
                    __nanosleep(200);
                    v = ld_relaxed(p);
                    if (++it > SPIN_LIMIT) __trap();
                }
                x = __uint_as_float((uint32_t)v);
                st_relaxed(p, 0.f, 0);
            }
            __syncwarp();
            asm volatile("fence.acq_rel.gpu;" ::: "memory");
            float mi[4], li[4];
#pragma unroll
            for (int i = 0; i < 4; i++) {
                mi[i] = __shfl_sync(0xffffffffu, x, 4 * i + h);
                li[i] = __shfl_sync(0xffffffffu, x, 4 * i + 2 + h);
            }
            const float s_t = h ? st[1] : st[0];
            const float M = fmaxf(fmaxf(fmaxf(mi[0], mi[1]), fmaxf(mi[2], mi[3])), s_t);
            float e[5], L;
            e[4] = ex2((s_t - M) * LOG2E);
            L = e[4];
#pragma unroll
            for (int i = 0; i < 4; i++) { e[i] = ex2((mi[i] - M) * LOG2E); L += e[i] * li[i]; }
            const float inv = 1.0f / L;
            if (lane < 2) {
#pragma unroll
                for (int i = 0; i < 5; i++) misc.wgt[h][i] = e[i] * inv;
                if (XMODE & 8) misc.wgt[h][0] = (split == 0 ? e[0] : split == 1 ? e[1] : split == 2 ? e[2] : e[3]) * inv;
            }
            __syncwarp();
            if (lane == 0) mbar_arrive(smem_u32(&misc.wready));
        }
    } else {
        const int tid = threadIdx.x - 64;
        const int g = lane >> 2, t = lane & 3;
        uint32_t qf[8][2];
        {
            const uint32_t* qp = reinterpret_cast<const uint32_t*>(q + (2 * bh + (g & 1)) * HD) + t;
#pragma unroll
            for (int j = 0; j < 8; j++) { qf[j][0] = __ldg(qp + 8 * j); qf[j][1] = __ldg(qp + 8 * j + 4); }
        }
        const int oh = t & 1, od = 16 * warp + g + 8 * (t >> 1);
        float vt = 0.f;
        if (split == 0) vt = __bfloat162float(v_tree[bh * HD + od]);
        __syncthreads();

        int s = 0, ph = 0;
        const uint32_t pb = smem_u32(pbuf);
        float mx = -INFINITY;
        {
            static_assert(KG % NCW == 0, "every warp scores KG / NCW key groups of a tile");
            const uint32_t x = (lane >> 4) ^ (lane & 7);
            const uint32_t soff = oh * 64 + (g >> 1) * 16 + (2 * (t >> 1) + (g & 1)) * 2;
#pragma unroll 1
            for (int i = 0; i < NT; i++) {
#pragma unroll
                for (int kk = 0; kk < KG / NCW; kk++) {
                    const int kgw = warp + kk * NCW;
                    if (kk == 0) mbar_wait(full0 + 8 * s, ph);
                    if (i == 0 && tid == 0) TSTAMP(2);
                    const uint32_t base = ring + s * TB + kgw * 4096 + ((lane >> 3) & 1) * 2048 + (lane & 7) * 128;
                    float c0[4] = {0.f, 0.f, 0.f, 0.f}, c1[4] = {0.f, 0.f, 0.f, 0.f};
                    uint32_t a[8][4];
#pragma unroll
                    for (int j = 0; j < 8; j++) ldsm4(a[j], base + (j >> 2) * 1024 + (((2 * (j & 3)) ^ x) << 4));
#pragma unroll
                    for (int j = 0; j < 8; j += 2) {
                        mma16816(c0, a[j], qf[j][0], qf[j][1]);
                        mma16816(c1, a[j + 1], qf[j + 1][0], qf[j + 1][1]);
                    }
                    if (kk == KG / NCW - 1) {
                        __syncwarp();
                        if (lane == 0) mbar_arrive(empty0 + 8 * s);
                    }
                    const float lo = (t & 1) ? c0[1] + c1[1] : c0[0] + c1[0];
                    const float hi = (t & 1) ? c0[3] + c1[3] : c0[2] + c1[2];
                    const __nv_bfloat16 sb = __float2bfloat16_rn(bf16r((t & 2) ? hi : lo) * SCALE);
                    mx = fmaxf(mx, __bfloat162float(sb));
                    const int gi = i * KG + kgw;
                    asm volatile("st.shared.b16 [%0], %1;" ::"r"(pb + (gi >> 1) * 128 + (gi & 1) * 8 + soff), "h"(__bfloat16_as_ushort(sb)) : "memory");
                }
                if (++s == STAGES) { s = 0; ph ^= 1; }
            }
        }
        if (tid == 0) TSTAMP(3);
        unsigned long long* slot = &g_part[bh][split == 0 ? 0 : split - 1][tid];
        __nv_bfloat16* optr = out + (2 * bh + oh) * HD + od;
        if (XMODE & 8) { if (split == 0) *optr = __ushort_as_bfloat16(0); }
        else if (split != 0) st_relaxed(slot, 0.f, 0);
#pragma unroll
        for (int o = 2; o < 32; o <<= 1) mx = fmaxf(mx, __shfl_xor_sync(0xffffffffu, mx, o));
        if (lane < 2) misc.mred[warp][lane] = mx;
        named_sync(1, NCW * 32);
        {
            const int h = (tid >> 2) & 1;
            float m = misc.mred[0][h];
#pragma unroll
            for (int w = 1; w < NCW; w++) m = fmaxf(m, misc.mred[w][h]);
            float l = 0.f;
#pragma unroll
            for (int r = 0; r < KEYS * 4 / 16 / (NCW * 32); r++) {
                uint4* pp = reinterpret_cast<uint4*>(pbuf) + tid + r * NCW * 32;
                uint4 v = *pp;
                uint32_t* u = reinterpret_cast<uint32_t*>(&v);
#pragma unroll
                for (int e = 0; e < 4; e++) {
                    const float p0 = ex2((bf_lo(u[e]) - m) * LOG2E), p1 = ex2((bf_hi(u[e]) - m) * LOG2E);
                    l += p0 + p1;
                    u[e] = pack_bf16(p0, p1);
                }
                *pp = v;
            }
            l += __shfl_xor_sync(0xffffffffu, l, 1);
            l += __shfl_xor_sync(0xffffffffu, l, 2);
            l += __shfl_xor_sync(0xffffffffu, l, 8);
            l += __shfl_xor_sync(0xffffffffu, l, 16);
            if ((lane & ~4) == 0) misc.lred[warp][lane >> 2] = l;
        }
        named_sync(2, (NCW + 1) * 32);
        if (tid == 0) TSTAMP(4);

        float o0[4] = {0.f, 0.f, 0.f, 0.f}, o1[4] = {0.f, 0.f, 0.f, 0.f};
        const uint32_t voff = (lane >> 4) * 2048 + (warp >> 2) * 1024 + (lane & 7) * 128 +
                              ((((2 * warp + ((lane >> 3) & 1)) & 7) ^ (lane & 7)) << 4);
        const uint32_t poff = pb + (g & 1) * 64 + t * 16;
        float4 w = make_float4(0.f, 0.f, 0.f, 0.f);
        unsigned long long r0 = 0, r1 = 0, r2 = 0;
        uint4 pf[KG / 2];
        auto load_p = [&](int i) {
#pragma unroll
            for (int kp = 0; kp < KG / 2; kp++)
                asm volatile("ld.shared.v4.u32 {%0,%1,%2,%3}, [%4];" : "=r"(pf[kp].x), "=r"(pf[kp].y), "=r"(pf[kp].z), "=r"(pf[kp].w)
                             : "r"(poff + (i * (KG / 2) + kp) * 128));
        };
#pragma unroll 1
        for (int i = 0; i < NT - 1; i++) {
            load_p(i);
            mbar_wait(full0 + 8 * s, ph);
            const uint32_t base = ring + s * TB + voff;
            uint32_t a[KG][4];
#pragma unroll
            for (int kg = 0; kg < KG; kg++) ldsm4t(a[kg], base + kg * 4096);
#pragma unroll
            for (int kp = 0; kp < KG / 2; kp++) {
                mma16816(o0, a[2 * kp], pf[kp].x, pf[kp].y);
                mma16816(o1, a[2 * kp + 1], pf[kp].z, pf[kp].w);
            }
            __syncwarp();
            if (lane == 0) mbar_arrive(empty0 + 8 * s);
            if (++s == STAGES) { s = 0; ph ^= 1; }
        }
        load_p(NT - 1);
        if (split == 0 || (XMODE & 8)) {
            mbar_wait(smem_u32(&misc.wready), 0);
            w = *reinterpret_cast<const float4*>(&misc.wgt[oh][0]);
            vt *= misc.wgt[oh][4];
            if (!(XMODE & 12)) { r0 = ld_relaxed(slot); r1 = ld_relaxed(slot + NCW * 32); r2 = ld_relaxed(slot + 2 * NCW * 32); }
        }
#pragma unroll
        for (int j = 0; j < SUB; j++) {
            mbar_wait(tail0 + 8 * j, 0);
            if (j == SUB - 1 && tid == 0) TSTAMP(5);
            const uint32_t base = ring + s * TB + j * SB + voff;
            uint32_t a[SKG][4];
#pragma unroll
            for (int kg = 0; kg < SKG; kg++) ldsm4t(a[kg], base + kg * 4096);
#pragma unroll
            for (int kg = 0; kg < SKG; kg++) {
                const int k = j * SKG + kg;
                if (k & 1) mma16816(o1, a[kg], pf[k / 2].z, pf[k / 2].w);
                else mma16816(o0, a[kg], pf[k / 2].x, pf[k / 2].y);
            }
        }
        const float lo = (t & 1) ? o0[1] + o1[1] : o0[0] + o1[0];
        const float hi = (t & 1) ? o0[3] + o1[3] : o0[2] + o1[2];
        const float mine = (t & 2) ? hi : lo;
        if (XMODE & 8) {
            const float own = fmaf(w.x, mine, vt);
            if (XMODE & 32) {
                const float nb = __shfl_xor_sync(0xffffffffu, own, 4);
                if (!(g & 1)) asm volatile("red.relaxed.gpu.global.add.noftz.bf16x2 [%0], %1;" ::"l"(optr), "r"(pack_bf16(own, nb)) : "memory");
            } else {
                asm volatile("red.relaxed.gpu.global.add.noftz.bf16 [%0], %1;" ::"l"(optr), "h"(__bfloat16_as_ushort(__float2bfloat16_rn(own))) : "memory");
            }
        } else if (split != 0) {
            st_relaxed(slot, mine, 1);
            if (tid == 0) TSTAMP(6);
        } else {
            const float own = fmaf(w.x, mine, vt);
            uint32_t it = 0;
            if (tid == 0 && own != 123.456f) TSTAMP(6);
            if ((XMODE & 16) && ((r0 >> 32) == 0 || (r1 >> 32) == 0 || (r2 >> 32) == 0)) {
                unsigned long long a[3][3];
#pragma unroll
                for (int u = 0; u < 3; u++) {
                    a[u][0] = ld_relaxed(slot); a[u][1] = ld_relaxed(slot + NCW * 32); a[u][2] = ld_relaxed(slot + 2 * NCW * 32);
                    if (u < 2) { const uint32_t c0 = clock(); while ((uint32_t)clock() - c0 < 110) {} }
                }
                while (true) {
                    bool done = false;
#pragma unroll
                    for (int u = 0; u < 3; u++) {
                        if (!done) {
                            done = (a[u][0] >> 32) != 0 && (a[u][1] >> 32) != 0 && (a[u][2] >> 32) != 0;
                            if (done) { r0 = a[u][0]; r1 = a[u][1]; r2 = a[u][2]; }
                            else { a[u][0] = ld_relaxed(slot); a[u][1] = ld_relaxed(slot + NCW * 32); a[u][2] = ld_relaxed(slot + 2 * NCW * 32); }
                        }
                    }
                    if (done) break;
                    if (++it > SPIN_LIMIT) __trap();
                }
            }
            while (!(XMODE & 17) && ((r0 >> 32) == 0 || (r1 >> 32) == 0 || (r2 >> 32) == 0)) {
                if (XMODE >> 8) __nanosleep(XMODE >> 8);
                if ((r0 >> 32) == 0) r0 = ld_relaxed(slot);
                if ((r1 >> 32) == 0) r1 = ld_relaxed(slot + NCW * 32);
                if ((r2 >> 32) == 0) r2 = ld_relaxed(slot + 2 * NCW * 32);
                if (++it > SPIN_LIMIT) __trap();
            }
            const float r = fmaf(w.w, __uint_as_float((uint32_t)r2),
                            fmaf(w.z, __uint_as_float((uint32_t)r1), fmaf(w.y, __uint_as_float((uint32_t)r0), own)));
            *optr = __float2bfloat16_rn(r);
            if (tid == 0) TSTAMP(7);
        }
    }
}

typedef CUresult (*EncodeFn)(CUtensorMap*, CUtensorMapDataType, cuuint32_t, void*, const cuuint64_t*, const cuuint64_t*,
                             const cuuint32_t*, const cuuint32_t*, CUtensorMapInterleave, CUtensorMapSwizzle,
                             CUtensorMapL2promotion, CUtensorMapFloatOOBfill);

static void make_map(CUtensorMap* m, const void* base, int tile, int promo) {
    static EncodeFn enc = nullptr;
    if (!enc) {
        cudaDriverEntryPointQueryResult qr;
        cudaGetDriverEntryPoint("cuTensorMapEncodeTiled", (void**)&enc, cudaEnableDefault, &qr);
    }
    cuuint64_t gd[4] = {64, 8, 2, (cuuint64_t)NHEAD * CTX / 8};
    cuuint64_t gs[3] = {256, 128, 2048};
    cuuint32_t bd[4] = {64, 8, 2, (cuuint32_t)tile / 8};
    cuuint32_t es[4] = {1, 1, 1, 1};
    enc(m, CU_TENSOR_MAP_DATA_TYPE_BFLOAT16, 4, const_cast<void*>(base), gd, gs, bd, es, CU_TENSOR_MAP_INTERLEAVE_NONE,
        CU_TENSOR_MAP_SWIZZLE_128B, (CUtensorMapL2promotion)promo, CU_TENSOR_MAP_FLOAT_OOB_FILL_NONE);
}

template <int TILE, int STAGES, int INFLIGHT, int SUB, int HINT, int XMODE = 0>
static void launch(void* const* d_in, void* d_out, int promo, cudaStream_t stream) {
    auto kern = tree_attn_kernel<TILE, STAGES, INFLIGHT, SUB, HINT, XMODE>;
    constexpr int smem = smem_bytes<TILE, STAGES>();
    cudaFuncSetAttribute(kern, cudaFuncAttributeMaxDynamicSharedMemorySize, smem);
    CUtensorMap mk, mv, mvt;
    make_map(&mk, d_in[1], TILE, promo);
    make_map(&mv, d_in[2], TILE, promo);
    make_map(&mvt, d_in[2], TILE / SUB, promo);
    kern<<<NHEAD * NSPLIT, NTHREADS, smem, stream>>>(mk, mv, mvt, (const __nv_bfloat16*)d_in[0], (const __nv_bfloat16*)d_in[3],
                                                     (const __nv_bfloat16*)d_in[4], (const __nv_bfloat16*)d_in[5],
                                                     (__nv_bfloat16*)d_out);
}

}

extern "C" void kernel_launch(void* const* d_in, const int* in_sizes, int n_in, void* d_out, int out_size) {
    (void)in_sizes; (void)n_in; (void)out_size;
    ta::launch<128, 3, 3, 1, 1, 40>(d_in, d_out, 2, cudaStreamPerThread);
}
```

```cpp
#include <cuda_runtime.h>
#include <cuda_bf16.h>
#include <cuda.h>
#include <stdint.h>

namespace ta {

constexpr int NB = 2, HKV = 16, CTX = 8192, HD = 128;
constexpr int NHEAD = NB * HKV;
constexpr int NSPLIT = 4;
constexpr int KEYS = CTX / NSPLIT;
constexpr int TILE = 128;
constexpr int NT = KEYS / TILE;
constexpr int TB = TILE * HD * 2;
constexpr int NCW = 8;
constexpr int NTHREADS = (NCW + 2) * 32;
constexpr float LOG2E = 1.4426950408889634f;
constexpr float SCALE = 0.08838834764831845f;
constexpr uint32_t SPIN_LIMIT = 1u << 24;
constexpr uint64_t EVICT_FIRST = 0x12F0000000000000ull;

__device__ unsigned long long g_ml[NHEAD][NSPLIT][NSPLIT][4];

__device__ __forceinline__ uint32_t smem_u32(const void* p) { return (uint32_t)__cvta_generic_to_shared(p); }
__device__ __forceinline__ void mbar_init(uint32_t bar, uint32_t cnt) {
    asm volatile("mbarrier.init.shared::cta.b64 [%0], %1;" ::"r"(bar), "r"(cnt) : "memory");
}
__device__ __forceinline__ void mbar_expect_tx(uint32_t bar, uint32_t bytes) {
    asm volatile("mbarrier.arrive.expect_tx.shared::cta.b64 _, [%0], %1;" ::"r"(bar), "r"(bytes) : "memory");
}
__device__ __forceinline__ void mbar_arrive(uint32_t bar) {
    asm volatile("mbarrier.arrive.shared::cta.b64 _, [%0];" ::"r"(bar) : "memory");
}
__device__ __forceinline__ void mbar_wait(uint32_t bar, uint32_t parity) {
    uint32_t ok, it = 0;
    do {
        asm volatile("{\n\t.reg .pred p;\n\tmbarrier.try_wait.parity.shared::cta.b64 p, [%1], %2;\n\tselp.u32 %0, 1, 0, p;\n\t}"
                     : "=r"(ok) : "r"(bar), "r"(parity) : "memory");
        if (++it > SPIN_LIMIT) __trap();
    } while (!ok);
}
__device__ __forceinline__ void named_sync(int id, int n) { asm volatile("bar.sync %0, %1;" ::"r"(id), "r"(n) : "memory"); }
__device__ __forceinline__ bool elect_one() {
    uint32_t p;
    asm volatile("{\n\t.reg .pred p;\n\telect.sync _|p, 0xffffffff;\n\tselp.u32 %0, 1, 0, p;\n\t}" : "=r"(p));
    return p != 0;
}
__device__ __forceinline__ void ldsm4(uint32_t (&r)[4], uint32_t a) {
    asm volatile("ldmatrix.sync.aligned.m8n8.x4.shared.b16 {%0,%1,%2,%3}, [%4];"
                 : "=r"(r[0]), "=r"(r[1]), "=r"(r[2]), "=r"(r[3]) : "r"(a) : "memory");
}
__device__ __forceinline__ void ldsm4t(uint32_t (&r)[4], uint32_t a) {
    asm volatile("ldmatrix.sync.aligned.m8n8.x4.trans.shared.b16 {%0,%1,%2,%3}, [%4];"
                 : "=r"(r[0]), "=r"(r[1]), "=r"(r[2]), "=r"(r[3]) : "r"(a) : "memory");
}
__device__ __forceinline__ void mma16816(float (&c)[4], const uint32_t (&a)[4], uint32_t b0, uint32_t b1) {
    asm volatile("mma.sync.aligned.m16n8k16.row.col.f32.bf16.bf16.f32 {%0,%1,%2,%3}, {%4,%5,%6,%7}, {%8,%9}, {%0,%1,%2,%3};"
                 : "+f"(c[0]), "+f"(c[1]), "+f"(c[2]), "+f"(c[3])
                 : "r"(a[0]), "r"(a[1]), "r"(a[2]), "r"(a[3]), "r"(b0), "r"(b1));
}
__device__ __forceinline__ unsigned long long ld_acquire(const unsigned long long* p) {
    unsigned long long v;
    asm volatile("ld.acquire.gpu.global.b64 %0, [%1];" : "=l"(v) : "l"(p) : "memory");
    return v;
}
__device__ __forceinline__ void st_relaxed(unsigned long long* p, float x, uint32_t flag) {
    unsigned long long v = ((unsigned long long)flag << 32) | __float_as_uint(x);
    asm volatile("st.relaxed.gpu.global.b64 [%0], %1;" ::"l"(p), "l"(v) : "memory");
}
__device__ __forceinline__ float bf16r(float x) { return __bfloat162float(__float2bfloat16_rn(x)); }
__device__ __forceinline__ float bf_lo(uint32_t x) { return __uint_as_float(x << 16); }
__device__ __forceinline__ float bf_hi(uint32_t x) { return __uint_as_float(x & 0xffff0000u); }
__device__ __forceinline__ uint32_t pack_bf16(float lo, float hi) {
    uint32_t r;
    asm("cvt.rn.bf16x2.f32 %0, %1, %2;" : "=r"(r) : "f"(hi), "f"(lo));
    return r;
}
__device__ __forceinline__ float ex2(float x) {
    float r;
    asm("ex2.approx.ftz.f32 %0, %1;" : "=f"(r) : "f"(x));
    return r;
}

template <int N> struct IC { static constexpr int value = N; };

struct __align__(16) Misc {
    float wgt[2][2];
    float mred[NCW][2];
    float lred[NCW][2];
    unsigned long long full[8];
    unsigned long long empty[8];
    unsigned long long wready;
};

template <int STAGES>
constexpr int smem_bytes() { return STAGES * TB + KEYS * 4 + (int)sizeof(Misc); }

template <int STAGES, int INFLIGHT, int NHE, int PFW>
__global__ void __launch_bounds__(NTHREADS, 1)
tree_attn_kernel(const __nv_bfloat16* __restrict__ k_cache, const __nv_bfloat16* __restrict__ q,
                 const __nv_bfloat16* __restrict__ k_tree, const __nv_bfloat16* __restrict__ v_tree,
                 const __nv_bfloat16* __restrict__ tree_mask, __nv_bfloat16* __restrict__ out,
                 const __grid_constant__ CUtensorMap map_k, const __grid_constant__ CUtensorMap map_v,
                 const __grid_constant__ CUtensorMap map_vh) {
    constexpr int NF = NT - NHE / 2;
    constexpr int NE = NT + NF + NHE;
    extern __shared__ __align__(1024) unsigned char smem[];
    unsigned char* pbuf = smem + STAGES * TB;
    Misc& misc = *reinterpret_cast<Misc*>(smem + STAGES * TB + KEYS * 4);

    const int bh = blockIdx.x / NSPLIT, split = blockIdx.x % NSPLIT;
    const uint32_t ring = smem_u32(smem);
    const uint32_t full0 = smem_u32(&misc.full[0]), empty0 = smem_u32(&misc.empty[0]);
    const int row0 = blockIdx.x * (KEYS / 8);

    auto issue = [&](const CUtensorMap* m, int half_tile, int s, uint32_t bytes) {
        mbar_expect_tx(full0 + 8 * s, bytes);
        asm volatile("cp.async.bulk.tensor.4d.shared::cluster.global.mbarrier::complete_tx::bytes.L2::cache_hint [%0], [%1, {%3, %3, %3, %4}], [%2], %5;"
                     ::"r"(ring + s * TB), "l"(m), "r"(full0 + 8 * s), "r"(0), "r"(row0 + half_tile * (TILE / 16)), "l"(EVICT_FIRST) : "memory");
    };

    if (threadIdx.x < PFW * 32)
        asm volatile("prefetch.global.L2 [%0];" ::"l"(reinterpret_cast<const char*>(k_cache) + (size_t)blockIdx.x * (KEYS * HD * 2) + threadIdx.x * 128) : "memory");
    if (threadIdx.x < 32) {
        if (elect_one()) {
#pragma unroll
            for (int s = 0; s < STAGES; s++) mbar_init(full0 + 8 * s, 1);
            asm volatile("fence.mbarrier_init.release.cluster;" ::: "memory");
#pragma unroll
            for (int i = 0; i < INFLIGHT; i++) issue(&map_k, 2 * i, i, TB);
#pragma unroll
            for (int s = 0; s < STAGES; s++) mbar_init(empty0 + 8 * s, NCW);
            mbar_init(smem_u32(&misc.wready), 1);
            asm volatile("prefetch.tensormap [%0];" ::"l"(&map_v) : "memory");
            asm volatile("prefetch.tensormap [%0];" ::"l"(&map_vh) : "memory");
        }
        __syncwarp();
    }

    const int lane = threadIdx.x & 31;
    const int warp = __shfl_sync(0xffffffffu, (int)(threadIdx.x >> 5), 0) - 2;
    if (warp == -2) {
        __syncthreads();
        if (elect_one()) {
            int s = INFLIGHT % STAGES, ph = (INFLIGHT / STAGES) & 1;
            int sf = 0, phf = 0;
#pragma unroll 1
            for (int i = INFLIGHT; i < NE; i++) {
                if (INFLIGHT < STAGES) {
                    mbar_wait(full0 + 8 * sf, phf);
                    if (++sf == STAGES) { sf = 0; phf ^= 1; }
                }
                if (i >= STAGES) mbar_wait(empty0 + 8 * s, ph ^ 1);
                if (i < NT + NF) issue(i < NT ? &map_k : &map_v, 2 * (i % NT), s, TB);
                else issue(&map_vh, NF + i - NT, s, TB / 2);
                if (++s == STAGES) { s = 0; ph ^= 1; }
            }
        }
    } else if (warp == -1) {
        __syncthreads();
        reinterpret_cast<uint32_t*>(out + 2 * bh * HD)[split * 32 + lane] = 0u;
        float st[2];
        {
            const uint2 kt = *reinterpret_cast<const uint2*>(k_tree + bh * HD + lane * 4);
            const float mk = __bfloat162float(tree_mask[bh / HKV]);
            const float madd = bf16r(bf16r(1.0f - mk) * -1000000000.0f);
#pragma unroll
            for (int h = 0; h < 2; h++) {
                const uint2 qv = *reinterpret_cast<const uint2*>(q + (2 * bh + h) * HD + lane * 4);
                float a = bf_lo(qv.x) * bf_lo(kt.x) + bf_hi(qv.x) * bf_hi(kt.x) + bf_lo(qv.y) * bf_lo(kt.y) + bf_hi(qv.y) * bf_hi(kt.y);
#pragma unroll
                for (int o = 16; o > 0; o >>= 1) a += __shfl_xor_sync(0xffffffffu, a, o);
                st[h] = bf16r(bf16r(bf16r(a) * SCALE) + madd);
            }
        }
        __syncwarp();
        asm volatile("fence.acq_rel.gpu;" ::: "memory");
        named_sync(2, (NCW + 1) * 32);
        const int h = lane & 1, peer = lane >> 2;
        float m = misc.mred[0][h], l = misc.lred[0][h];
#pragma unroll
        for (int w = 1; w < NCW; w++) { m = fmaxf(m, misc.mred[w][h]); l += misc.lred[w][h]; }
        float x = (lane & 2) ? l : m;
        if (peer < NSPLIT && peer != split) {
            st_relaxed(&g_ml[bh][peer][split][lane & 3], x, 1);
            unsigned long long* p = &g_ml[bh][split][peer][lane & 3];
            unsigned long long v = ld_acquire(p);
            uint32_t it = 0;
            while ((v >> 32) == 0) {
                __nanosleep(500);
                v = ld_acquire(p);
                if (++it > SPIN_LIMIT) __trap();
            }
            x = __uint_as_float((uint32_t)v);
            st_relaxed(p, 0.f, 0);
        }
        __syncwarp();
        const float s_t = h ? st[1] : st[0];
        float mi[NSPLIT], M = s_t;
#pragma unroll
        for (int i = 0; i < NSPLIT; i++) { mi[i] = __shfl_sync(0xffffffffu, x, 4 * i + h); M = fmaxf(M, mi[i]); }
        const float et = ex2((s_t - M) * LOG2E);
        float L = et;
#pragma unroll
        for (int i = 0; i < NSPLIT; i++) L = fmaf(ex2((mi[i] - M) * LOG2E), __shfl_sync(0xffffffffu, x, 4 * i + 2 + h), L);
        const float inv = 1.0f / L;
        if (lane < 2) {
            misc.wgt[h][0] = ex2((m - M) * LOG2E) * inv;
            misc.wgt[h][1] = split == 0 ? et * inv : 0.f;
        }
        __syncwarp();
        if (lane == 0) mbar_arrive(smem_u32(&misc.wready));
    } else {
        const int tid = threadIdx.x - 64;
        const int g = lane >> 2, t = lane & 3;
        uint32_t qf[8][2];
        {
            const uint32_t* qp = reinterpret_cast<const uint32_t*>(q + (2 * bh + (g & 1)) * HD) + t;
#pragma unroll
            for (int j = 0; j < 8; j++) { qf[j][0] = __ldg(qp + 8 * j); qf[j][1] = __ldg(qp + 8 * j + 4); }
        }
        const int oh = t & 1, od = 16 * warp + g + 8 * (t >> 1);
        unsigned short vt_raw;
        asm volatile("ld.global.nc.u16 %0, [%1];" : "=h"(vt_raw) : "l"(v_tree + bh * HD + od));
        __syncthreads();

        int s = 0, ph = 0;
        const uint32_t pb = smem_u32(pbuf);
        float mx = -INFINITY;
        {
            const uint32_t koff = ring + warp * 4096 + ((lane >> 3) & 1) * 2048 + (lane & 7) * 128;
            const uint32_t x = (lane >> 4) ^ (lane & 7);
            uint32_t sp = pb + (warp >> 1) * 128 + (warp & 1) * 8 + oh * 64 + (g >> 1) * 16 + (2 * (t >> 1) + (g & 1)) * 2;
#pragma unroll 1
            for (int i = 0; i < NT; i++) {
                mbar_wait(full0 + 8 * s, ph);
                float c0[4] = {0.f, 0.f, 0.f, 0.f}, c1[4] = {0.f, 0.f, 0.f, 0.f};
                uint32_t a[8][4];
#pragma unroll
                for (int j = 0; j < 8; j++) ldsm4(a[j], koff + s * TB + (j >> 2) * 1024 + (((2 * (j & 3)) ^ x) << 4));
#pragma unroll
                for (int j = 0; j < 8; j += 2) {
                    mma16816(c0, a[j], qf[j][0], qf[j][1]);
                    mma16816(c1, a[j + 1], qf[j + 1][0], qf[j + 1][1]);
                }
                __syncwarp();
                if (lane == 0) mbar_arrive(empty0 + 8 * s);
                const float lo = (t & 1) ? c0[1] + c1[1] : c0[0] + c1[0];
                const float hi = (t & 1) ? c0[3] + c1[3] : c0[2] + c1[2];
                const __nv_bfloat16 sb = __float2bfloat16_rn(bf16r((t & 2) ? hi : lo) * SCALE);
                mx = fmaxf(mx, __bfloat162float(sb));
                asm volatile("st.shared.b16 [%0], %1;" ::"r"(sp), "h"(__bfloat16_as_ushort(sb)) : "memory");
                sp += TILE * 4;
                if (++s == STAGES) { s = 0; ph ^= 1; }
            }
        }
#pragma unroll
        for (int o = 2; o < 32; o <<= 1) mx = fmaxf(mx, __shfl_xor_sync(0xffffffffu, mx, o));
        if (lane < 2) misc.mred[warp][lane] = mx;
        named_sync(1, NCW * 32);
        {
            const int h = (tid >> 2) & 1;
            float m = misc.mred[0][h];
#pragma unroll
            for (int w = 1; w < NCW; w++) m = fmaxf(m, misc.mred[w][h]);
            float l = 0.f;
#pragma unroll
            for (int r = 0; r < KEYS * 4 / 16 / (NCW * 32); r++) {
                uint4* pp = reinterpret_cast<uint4*>(pbuf) + tid + r * NCW * 32;
                uint4 v = *pp;
                uint32_t* u = reinterpret_cast<uint32_t*>(&v);
#pragma unroll
                for (int e = 0; e < 4; e++) {
                    const float p0 = ex2((bf_lo(u[e]) - m) * LOG2E), p1 = ex2((bf_hi(u[e]) - m) * LOG2E);
                    l += p0 + p1;
                    u[e] = pack_bf16(p0, p1);
                }
                *pp = v;
            }
            l += __shfl_xor_sync(0xffffffffu, l, 1);
            l += __shfl_xor_sync(0xffffffffu, l, 2);
            l += __shfl_xor_sync(0xffffffffu, l, 8);
            l += __shfl_xor_sync(0xffffffffu, l, 16);
            if ((lane & ~4) == 0) misc.lred[warp][lane >> 2] = l;
        }
        named_sync(2, (NCW + 1) * 32);

        float o0[4] = {0.f, 0.f, 0.f, 0.f}, o1[4] = {0.f, 0.f, 0.f, 0.f};
        const uint32_t voff = ring + (lane >> 4) * 2048 + (warp >> 2) * 1024 + (lane & 7) * 128 +
                              ((((2 * warp + ((lane >> 3) & 1)) & 7) ^ (lane & 7)) << 4);
        uint32_t poff = pb + (g & 1) * 64 + t * 16;
        __nv_bfloat16* optr = out + (2 * bh + oh) * HD + od;
        float w = 0.f, vt = 0.f;
        auto pv = [&](auto nk, bool last) {
            constexpr int NK = decltype(nk)::value;
            uint4 pf[NK];
#pragma unroll
            for (int kp = 0; kp < NK; kp++)
                asm volatile("ld.shared.v4.u32 {%0,%1,%2,%3}, [%4];" : "=r"(pf[kp].x), "=r"(pf[kp].y), "=r"(pf[kp].z), "=r"(pf[kp].w)
                             : "r"(poff + kp * 128));
            poff += NK * 128;
            if (last) {
                mbar_wait(smem_u32(&misc.wready), 0);
                const float2 ww = *reinterpret_cast<const float2*>(&misc.wgt[oh][0]);
                w = ww.x;
                vt = __bfloat162float(__ushort_as_bfloat16(vt_raw)) * ww.y;
            }
            mbar_wait(full0 + 8 * s, ph);
            uint32_t a[2 * NK][4];
#pragma unroll
            for (int kg = 0; kg < 2 * NK; kg++) ldsm4t(a[kg], voff + s * TB + kg * 4096);
#pragma unroll
            for (int kp = 0; kp < NK; kp++) {
                mma16816(o0, a[2 * kp], pf[kp].x, pf[kp].y);
                mma16816(o1, a[2 * kp + 1], pf[kp].z, pf[kp].w);
            }
            __syncwarp();
            if (lane == 0) mbar_arrive(empty0 + 8 * s);
            if (++s == STAGES) { s = 0; ph ^= 1; }
        };
#pragma unroll 1
        for (int i = 0; i < NF; i++) pv(IC<4>{}, false);
#pragma unroll 1
        for (int i = 0; i < NHE; i++) pv(IC<2>{}, i == NHE - 1);
        const float lo = (t & 1) ? o0[1] + o1[1] : o0[0] + o1[0];
        const float hi = (t & 1) ? o0[3] + o1[3] : o0[2] + o1[2];
        const float own = fmaf(w, (t & 2) ? hi : lo, vt);
        const float nb = __shfl_xor_sync(0xffffffffu, own, 4);
        if (!(g & 1)) asm volatile("red.relaxed.gpu.global.add.noftz.bf16x2 [%0], %1;" ::"l"(optr), "r"(pack_bf16(own, nb)) : "memory");
    }
}

typedef CUresult (*EncodeFn)(CUtensorMap*, CUtensorMapDataType, cuuint32_t, void*, const cuuint64_t*, const cuuint64_t*,
                             const cuuint32_t*, const cuuint32_t*, CUtensorMapInterleave, CUtensorMapSwizzle,
                             CUtensorMapL2promotion, CUtensorMapFloatOOBfill);

static void make_map(CUtensorMap* m, const void* base, int tile, int promo) {
    static EncodeFn enc = nullptr;
    if (!enc) {
        cudaDriverEntryPointQueryResult qr;
        cudaGetDriverEntryPoint("cuTensorMapEncodeTiled", (void**)&enc, cudaEnableDefault, &qr);
    }
    cuuint64_t gd[4] = {64, 8, 2, (cuuint64_t)NHEAD * CTX / 8};
    cuuint64_t gs[3] = {256, 128, 2048};
    cuuint32_t bd[4] = {64, 8, 2, (cuuint32_t)tile / 8};
    cuuint32_t es[4] = {1, 1, 1, 1};
    enc(m, CU_TENSOR_MAP_DATA_TYPE_BFLOAT16, 4, const_cast<void*>(base), gd, gs, bd, es, CU_TENSOR_MAP_INTERLEAVE_NONE,
        CU_TENSOR_MAP_SWIZZLE_128B, (CUtensorMapL2promotion)promo, CU_TENSOR_MAP_FLOAT_OOB_FILL_NONE);
}

template <int STAGES, int INFLIGHT, int NHE, int PFW>
static void launch(void* const* d_in, void* d_out, int promo, cudaStream_t stream) {
    auto kern = tree_attn_kernel<STAGES, INFLIGHT, NHE, PFW>;
    constexpr int smem = smem_bytes<STAGES>();
    cudaFuncSetAttribute(kern, cudaFuncAttributeMaxDynamicSharedMemorySize, smem);
    CUtensorMap mk, mv, mvh;
    make_map(&mvh, d_in[2], TILE / 2, promo);
    make_map(&mk, d_in[1], TILE, promo);
    make_map(&mv, d_in[2], TILE, promo);
    kern<<<NHEAD * NSPLIT, NTHREADS, smem, stream>>>((const __nv_bfloat16*)d_in[1], (const __nv_bfloat16*)d_in[0],
                                                     (const __nv_bfloat16*)d_in[3], (const __nv_bfloat16*)d_in[4],
                                                     (const __nv_bfloat16*)d_in[5], (__nv_bfloat16*)d_out, mk, mv, mvh);
}

}

extern "C" void kernel_launch(void* const* d_in, const int* in_sizes, int n_in, void* d_out, int out_size) {
    (void)in_sizes; (void)n_in; (void)out_size;
    ta::launch<5, 4, 6, 6>(d_in, d_out, CU_TENSOR_MAP_L2_PROMOTION_L2_128B, cudaStreamPerThread);
}
```

```cpp
#include <cuda_runtime.h>
#include <cuda_bf16.h>
#include <cuda.h>
#include <stdint.h>

namespace ta {

constexpr int NB = 2, HKV = 16, CTX = 8192, HD = 128;
constexpr int NHEAD = NB * HKV;
constexpr int NSPLIT = 4;
constexpr int KEYS = CTX / NSPLIT;
constexpr int TILE = 128;
constexpr int NT = KEYS / TILE;
constexpr int TB = TILE * HD * 2;
constexpr int NCW = 8;
constexpr int NTHREADS = (NCW + 2) * 32;
constexpr float LOG2E = 1.4426950408889634f;
constexpr float SCALE = 0.08838834764831845f;
constexpr uint32_t SPIN_LIMIT = 1u << 24;
constexpr uint64_t EVICT_FIRST = 0x12F0000000000000ull;

__device__ unsigned long long g_ml[NHEAD][NSPLIT][NSPLIT][4];

__device__ __forceinline__ uint32_t smem_u32(const void* p) { return (uint32_t)__cvta_generic_to_shared(p); }
__device__ __forceinline__ void mbar_init(uint32_t bar, uint32_t cnt) {
    asm volatile("mbarrier.init.shared::cta.b64 [%0], %1;" ::"r"(bar), "r"(cnt) : "memory");
}
__device__ __forceinline__ void mbar_expect_tx(uint32_t bar, uint32_t bytes) {
    asm volatile("mbarrier.arrive.expect_tx.shared::cta.b64 _, [%0], %1;" ::"r"(bar), "r"(bytes) : "memory");
}
__device__ __forceinline__ void mbar_arrive(uint32_t bar) {
    asm volatile("mbarrier.arrive.shared::cta.b64 _, [%0];" ::"r"(bar) : "memory");
}
__device__ __forceinline__ void mbar_wait(uint32_t bar, uint32_t parity) {
    uint32_t ok, it = 0;
    do {
        asm volatile("{\n\t.reg .pred p;\n\tmbarrier.try_wait.parity.shared::cta.b64 p, [%1], %2;\n\tselp.u32 %0, 1, 0, p;\n\t}"
                     : "=r"(ok) : "r"(bar), "r"(parity) : "memory");
        if (++it > SPIN_LIMIT) __trap();
    } while (!ok);
}
__device__ __forceinline__ void named_sync(int id, int n) { asm volatile("bar.sync %0, %1;" ::"r"(id), "r"(n) : "memory"); }
__device__ __forceinline__ bool elect_one() {
    uint32_t p;
    asm volatile("{\n\t.reg .pred p;\n\telect.sync _|p, 0xffffffff;\n\tselp.u32 %0, 1, 0, p;\n\t}" : "=r"(p));
    return p != 0;
}
__device__ __forceinline__ void ldsm4(uint32_t (&r)[4], uint32_t a) {
    asm volatile("ldmatrix.sync.aligned.m8n8.x4.shared.b16 {%0,%1,%2,%3}, [%4];"
                 : "=r"(r[0]), "=r"(r[1]), "=r"(r[2]), "=r"(r[3]) : "r"(a) : "memory");
}
__device__ __forceinline__ void ldsm4t(uint32_t (&r)[4], uint32_t a) {
    asm volatile("ldmatrix.sync.aligned.m8n8.x4.trans.shared.b16 {%0,%1,%2,%3}, [%4];"
                 : "=r"(r[0]), "=r"(r[1]), "=r"(r[2]), "=r"(r[3]) : "r"(a) : "memory");
}
__device__ __forceinline__ void mma16816(float (&c)[4], const uint32_t (&a)[4], uint32_t b0, uint32_t b1) {
    asm volatile("mma.sync.aligned.m16n8k16.row.col.f32.bf16.bf16.f32 {%0,%1,%2,%3}, {%4,%5,%6,%7}, {%8,%9}, {%0,%1,%2,%3};"
                 : "+f"(c[0]), "+f"(c[1]), "+f"(c[2]), "+f"(c[3])
                 : "r"(a[0]), "r"(a[1]), "r"(a[2]), "r"(a[3]), "r"(b0), "r"(b1));
}
__device__ __forceinline__ unsigned long long ld_acquire(const unsigned long long* p) {
    unsigned long long v;
    asm volatile("ld.acquire.gpu.global.b64 %0, [%1];" : "=l"(v) : "l"(p) : "memory");
    return v;
}
__device__ __forceinline__ void st_relaxed(unsigned long long* p, float x, uint32_t flag) {
    unsigned long long v = ((unsigned long long)flag << 32) | __float_as_uint(x);
    asm volatile("st.relaxed.gpu.global.b64 [%0], %1;" ::"l"(p), "l"(v) : "memory");
}
__device__ __forceinline__ float bf16r(float x) { return __bfloat162float(__float2bfloat16_rn(x)); }
__device__ __forceinline__ float bf_lo(uint32_t x) { return __uint_as_float(x << 16); }
__device__ __forceinline__ float bf_hi(uint32_t x) { return __uint_as_float(x & 0xffff0000u); }
__device__ __forceinline__ uint32_t pack_bf16(float lo, float hi) {
    uint32_t r;
    asm("cvt.rn.bf16x2.f32 %0, %1, %2;" : "=r"(r) : "f"(hi), "f"(lo));
    return r;
}
__device__ __forceinline__ float ex2(float x) {
    float r;
    asm("ex2.approx.ftz.f32 %0, %1;" : "=f"(r) : "f"(x));
    return r;
}

template <int N> struct IC { static constexpr int value = N; };

struct __align__(16) Misc {
    float wgt[2][2];
    float mred[NCW][2];
    float lred[NCW][2];
    unsigned long long full[8];
    unsigned long long empty[8];
    unsigned long long lready;
    unsigned long long wready;
};

template <int STAGES>
constexpr int smem_bytes() { return STAGES * TB + KEYS * 4 + (int)sizeof(Misc); }

template <int STAGES, int INFLIGHT, int NHE, int PFW>
__global__ void __launch_bounds__(NTHREADS, 1)
tree_attn_kernel(const __nv_bfloat16* __restrict__ k_cache, const __nv_bfloat16* __restrict__ q,
                 const __nv_bfloat16* __restrict__ k_tree, const __nv_bfloat16* __restrict__ v_tree,
                 const __nv_bfloat16* __restrict__ tree_mask, __nv_bfloat16* __restrict__ out,
                 const __grid_constant__ CUtensorMap map_k, const __grid_constant__ CUtensorMap map_v,
                 const __grid_constant__ CUtensorMap map_vh) {
    constexpr int NF = NT - NHE / 2;
    constexpr int NE = NT + NF + NHE;
    extern __shared__ __align__(1024) unsigned char smem[];
    unsigned char* pbuf = smem + STAGES * TB;
    Misc& misc = *reinterpret_cast<Misc*>(smem + STAGES * TB + KEYS * 4);

    const int bh = blockIdx.x / NSPLIT, split = blockIdx.x % NSPLIT;
    const uint32_t ring = smem_u32(smem);
    const uint32_t full0 = smem_u32(&misc.full[0]), empty0 = smem_u32(&misc.empty[0]);
    const int row0 = blockIdx.x * (KEYS / 8);

    auto issue = [&](const CUtensorMap* m, int half_tile, int s, uint32_t bytes) {
        mbar_expect_tx(full0 + 8 * s, bytes);
        asm volatile("cp.async.bulk.tensor.4d.shared::cluster.global.mbarrier::complete_tx::bytes.L2::cache_hint [%0], [%1, {%3, %3, %3, %4}], [%2], %5;"
                     ::"r"(ring + s * TB), "l"(m), "r"(full0 + 8 * s), "r"(0), "r"(row0 + half_tile * (TILE / 16)), "l"(EVICT_FIRST) : "memory");
    };

    if (threadIdx.x < PFW * 32)
        asm volatile("prefetch.global.L2 [%0];" ::"l"(reinterpret_cast<const char*>(k_cache) + (size_t)blockIdx.x * (KEYS * HD * 2) + threadIdx.x * 128) : "memory");
    if (threadIdx.x < 32) {
        if (elect_one()) {
#pragma unroll
            for (int s = 0; s < STAGES; s++) mbar_init(full0 + 8 * s, 1);
            asm volatile("fence.mbarrier_init.release.cluster;" ::: "memory");
#pragma unroll
            for (int i = 0; i < INFLIGHT; i++) issue(&map_k, 2 * i, i, TB);
#pragma unroll
            for (int s = 0; s < STAGES; s++) mbar_init(empty0 + 8 * s, NCW);
            mbar_init(smem_u32(&misc.lready), 1);
            mbar_init(smem_u32(&misc.wready), 2);
            asm volatile("prefetch.tensormap [%0];" ::"l"(&map_v) : "memory");
            asm volatile("prefetch.tensormap [%0];" ::"l"(&map_vh) : "memory");
        }
        __syncwarp();
    }

    const int lane = threadIdx.x & 31;
    const int warp = __shfl_sync(0xffffffffu, (int)(threadIdx.x >> 5), 0) - 2;
    if (warp == -2) {
        named_sync(0, NTHREADS);
        if (elect_one()) {
            int s = INFLIGHT % STAGES, ph = (INFLIGHT / STAGES) & 1;
            int sf = 0, phf = 0;
#pragma unroll 1
            for (int i = INFLIGHT; i < NE; i++) {
                if (INFLIGHT < STAGES) {
                    mbar_wait(full0 + 8 * sf, phf);
                    if (++sf == STAGES) { sf = 0; phf ^= 1; }
                }
                if (i >= STAGES) mbar_wait(empty0 + 8 * s, ph ^ 1);
                if (i < NT + NF) issue(i < NT ? &map_k : &map_v, 2 * (i % NT), s, TB);
                else issue(&map_vh, NF + i - NT, s, TB / 2);
                if (++s == STAGES) { s = 0; ph ^= 1; }
            }
        }
    } else if (warp == -1) {
        reinterpret_cast<uint32_t*>(out + 2 * bh * HD)[split * 32 + lane] = 0u;
        const uint2 kt = __ldg(reinterpret_cast<const uint2*>(k_tree + bh * HD + lane * 4));
        const uint2 q0 = __ldg(reinterpret_cast<const uint2*>(q + 2 * bh * HD + lane * 4));
        const uint2 q1 = __ldg(reinterpret_cast<const uint2*>(q + (2 * bh + 1) * HD + lane * 4));
        const __nv_bfloat16 mk = __ldg(tree_mask + bh / HKV);
        named_sync(0, NTHREADS);
        asm volatile("fence.acq_rel.gpu;" ::: "memory");
        float st[2];
        const float madd = bf16r(bf16r(1.0f - __bfloat162float(mk)) * -1000000000.0f);
#pragma unroll
        for (int h = 0; h < 2; h++) {
            const uint2 qv = h ? q1 : q0;
            float a = bf_lo(qv.x) * bf_lo(kt.x) + bf_hi(qv.x) * bf_hi(kt.x) + bf_lo(qv.y) * bf_lo(kt.y) + bf_hi(qv.y) * bf_hi(kt.y);
#pragma unroll
            for (int o = 16; o > 0; o >>= 1) a += __shfl_xor_sync(0xffffffffu, a, o);
            st[h] = bf16r(bf16r(bf16r(a) * SCALE) + madd);
        }
        mbar_wait(smem_u32(&misc.lready), 0);
        const int h = lane & 1, peer = lane >> 2;
        float m = misc.mred[0][h], l = misc.lred[0][h];
#pragma unroll
        for (int w = 1; w < NCW; w++) { m = fmaxf(m, misc.mred[w][h]); l += misc.lred[w][h]; }
        float x = (lane & 2) ? l : m;
        if (peer < NSPLIT && peer != split) {
            st_relaxed(&g_ml[bh][peer][split][lane & 3], x, 1);
            unsigned long long* p = &g_ml[bh][split][peer][lane & 3];
            unsigned long long v = ld_acquire(p);
            uint32_t it = 0;
            while ((v >> 32) == 0) {
                __nanosleep(500);
                v = ld_acquire(p);
                if (++it > SPIN_LIMIT) __trap();
            }
            x = __uint_as_float((uint32_t)v);
            st_relaxed(p, 0.f, 0);
        }
        __syncwarp();
        const float s_t = h ? st[1] : st[0];
        float mi[NSPLIT], M = s_t;
#pragma unroll
        for (int i = 0; i < NSPLIT; i++) { mi[i] = __shfl_sync(0xffffffffu, x, 4 * i + h); M = fmaxf(M, mi[i]); }
        const float et = ex2((s_t - M) * LOG2E);
        float L = et;
#pragma unroll
        for (int i = 0; i < NSPLIT; i++) L = fmaf(ex2((mi[i] - M) * LOG2E), __shfl_sync(0xffffffffu, x, 4 * i + 2 + h), L);
        const float inv = 1.0f / L;
        if (lane < 2) {
            misc.wgt[h][0] = ex2((m - M) * LOG2E) * inv;
            misc.wgt[h][1] = et * inv;
            mbar_arrive(smem_u32(&misc.wready));
        }
    } else {
        const int tid = threadIdx.x - 64;
        const int g = lane >> 2, t = lane & 3;
        uint32_t qf[8][2];
        {
            const uint32_t* qp = reinterpret_cast<const uint32_t*>(q + (2 * bh + (g & 1)) * HD) + t;
#pragma unroll
            for (int j = 0; j < 8; j++) { qf[j][0] = __ldg(qp + 8 * j); qf[j][1] = __ldg(qp + 8 * j + 4); }
        }
        const int oh = t & 1, od = 16 * warp + g + 8 * (t >> 1);
        unsigned short vt_raw;
        asm volatile("ld.global.nc.u16 %0, [%1];" : "=h"(vt_raw) : "l"(v_tree + bh * HD + od));
        named_sync(0, NTHREADS);

        int s = 0, ph = 0;
        const uint32_t pb = smem_u32(pbuf);
        float mx = -INFINITY;
        {
            const uint32_t koff = ring + warp * 4096 + ((lane >> 3) & 1) * 2048 + (lane & 7) * 128;
            const uint32_t x = (lane >> 4) ^ (lane & 7);
            uint32_t sp = pb + (warp >> 1) * 128 + (warp & 1) * 8 + oh * 64 + (g >> 1) * 16 + (2 * (t >> 1) + (g & 1)) * 2;
#pragma unroll 1
            for (int i = 0; i < NT; i++) {
                mbar_wait(full0 + 8 * s, ph);
                float c0[4] = {0.f, 0.f, 0.f, 0.f}, c1[4] = {0.f, 0.f, 0.f, 0.f};
                uint32_t a[8][4];
#pragma unroll
                for (int j = 0; j < 8; j++) ldsm4(a[j], koff + s * TB + (j >> 2) * 1024 + (((2 * (j & 3)) ^ x) << 4));
#pragma unroll
                for (int j = 0; j < 8; j += 2) {
                    mma16816(c0, a[j], qf[j][0], qf[j][1]);
                    mma16816(c1, a[j + 1], qf[j + 1][0], qf[j + 1][1]);
                }
                __syncwarp();
                if (lane == 0) mbar_arrive(empty0 + 8 * s);
                const float lo = (t & 1) ? c0[1] + c1[1] : c0[0] + c1[0];
                const float hi = (t & 1) ? c0[3] + c1[3] : c0[2] + c1[2];
                const __nv_bfloat16 sb = __float2bfloat16_rn(bf16r((t & 2) ? hi : lo) * SCALE);
                mx = fmaxf(mx, __bfloat162float(sb));
                asm volatile("st.shared.b16 [%0], %1;" ::"r"(sp), "h"(__bfloat16_as_ushort(sb)) : "memory");
                sp += TILE * 4;
                if (++s == STAGES) { s = 0; ph ^= 1; }
            }
        }
#pragma unroll
        for (int o = 2; o < 32; o <<= 1) mx = fmaxf(mx, __shfl_xor_sync(0xffffffffu, mx, o));
        if (lane < 2) misc.mred[warp][lane] = mx;
        named_sync(1, NCW * 32);
        {
            const int h = (tid >> 2) & 1;
            float m = misc.mred[0][h];
#pragma unroll
            for (int w = 1; w < NCW; w++) m = fmaxf(m, misc.mred[w][h]);
            float l = 0.f;
#pragma unroll
            for (int r = 0; r < KEYS * 4 / 16 / (NCW * 32); r++) {
                uint4* pp = reinterpret_cast<uint4*>(pbuf) + tid + r * NCW * 32;
                uint4 v = *pp;
                uint32_t* u = reinterpret_cast<uint32_t*>(&v);
#pragma unroll
                for (int e = 0; e < 4; e++) {
                    const float p0 = ex2((bf_lo(u[e]) - m) * LOG2E), p1 = ex2((bf_hi(u[e]) - m) * LOG2E);
                    l += p0 + p1;
                    u[e] = pack_bf16(p0, p1);
                }
                *pp = v;
            }
            l += __shfl_xor_sync(0xffffffffu, l, 1);
            l += __shfl_xor_sync(0xffffffffu, l, 2);
            l += __shfl_xor_sync(0xffffffffu, l, 8);
            l += __shfl_xor_sync(0xffffffffu, l, 16);
            if ((lane & ~4) == 0) misc.lred[warp][lane >> 2] = l;
        }
        named_sync(1, NCW * 32);
        if (tid == 0) mbar_arrive(smem_u32(&misc.lready));

        float o0[4] = {0.f, 0.f, 0.f, 0.f}, o1[4] = {0.f, 0.f, 0.f, 0.f};
        const uint32_t voff = ring + (lane >> 4) * 2048 + (warp >> 2) * 1024 + (lane & 7) * 128 +
                              ((((2 * warp + ((lane >> 3) & 1)) & 7) ^ (lane & 7)) << 4);
        uint32_t poff = pb + (g & 1) * 64 + t * 16;
        __nv_bfloat16* optr = out + (2 * bh + oh) * HD + od;
        float w = 0.f, vt = 0.f;
        auto pv = [&](auto nk, bool last) {
            constexpr int NK = decltype(nk)::value;
            uint4 pf[NK];
#pragma unroll
            for (int kp = 0; kp < NK; kp++)
                asm volatile("ld.shared.v4.u32 {%0,%1,%2,%3}, [%4];" : "=r"(pf[kp].x), "=r"(pf[kp].y), "=r"(pf[kp].z), "=r"(pf[kp].w)
                             : "r"(poff + kp * 128));
            poff += NK * 128;
            if (last) {
                mbar_wait(smem_u32(&misc.wready), 0);
                const float2 ww = *reinterpret_cast<const float2*>(&misc.wgt[oh][0]);
                w = ww.x;
                if (split == 0) vt = __bfloat162float(__ushort_as_bfloat16(vt_raw)) * ww.y;
            }
            mbar_wait(full0 + 8 * s, ph);
            uint32_t a[2 * NK][4];
#pragma unroll
            for (int kg = 0; kg < 2 * NK; kg++) ldsm4t(a[kg], voff + s * TB + kg * 4096);
#pragma unroll
            for (int kp = 0; kp < NK; kp++) {
                mma16816(o0, a[2 * kp], pf[kp].x, pf[kp].y);
                mma16816(o1, a[2 * kp + 1], pf[kp].z, pf[kp].w);
            }
            __syncwarp();
            if (lane == 0) mbar_arrive(empty0 + 8 * s);
            if (++s == STAGES) { s = 0; ph ^= 1; }
        };
#pragma unroll 1
        for (int i = 0; i < NF; i++) pv(IC<4>{}, false);
#pragma unroll 1
        for (int i = 0; i < NHE; i++) pv(IC<2>{}, i == NHE - 1);
        const float lo = (t & 1) ? o0[1] + o1[1] : o0[0] + o1[0];
        const float hi = (t & 1) ? o0[3] + o1[3] : o0[2] + o1[2];
        const float own = fmaf(w, (t & 2) ? hi : lo, vt);
        const float nb = __shfl_xor_sync(0xffffffffu, own, 4);
        if (!(g & 1)) asm volatile("red.relaxed.gpu.global.add.noftz.bf16x2 [%0], %1;" ::"l"(optr), "r"(pack_bf16(own, nb)) : "memory");
    }
}

typedef CUresult (*EncodeFn)(CUtensorMap*, CUtensorMapDataType, cuuint32_t, void*, const cuuint64_t*, const cuuint64_t*,
                             const cuuint32_t*, const cuuint32_t*, CUtensorMapInterleave, CUtensorMapSwizzle,
                             CUtensorMapL2promotion, CUtensorMapFloatOOBfill);

static void make_map(CUtensorMap* m, const void* base, int tile, int promo) {
    static EncodeFn enc = nullptr;
    if (!enc) {
        cudaDriverEntryPointQueryResult qr;
        cudaGetDriverEntryPoint("cuTensorMapEncodeTiled", (void**)&enc, cudaEnableDefault, &qr);
    }
    cuuint64_t gd[4] = {64, 8, 2, (cuuint64_t)NHEAD * CTX / 8};
    cuuint64_t gs[3] = {256, 128, 2048};
    cuuint32_t bd[4] = {64, 8, 2, (cuuint32_t)tile / 8};
    cuuint32_t es[4] = {1, 1, 1, 1};
    enc(m, CU_TENSOR_MAP_DATA_TYPE_BFLOAT16, 4, const_cast<void*>(base), gd, gs, bd, es, CU_TENSOR_MAP_INTERLEAVE_NONE,
        CU_TENSOR_MAP_SWIZZLE_128B, (CUtensorMapL2promotion)promo, CU_TENSOR_MAP_FLOAT_OOB_FILL_NONE);
}

template <int STAGES, int INFLIGHT, int NHE, int PFW>
static void launch(void* const* d_in, void* d_out, int promo, cudaStream_t stream) {
    auto kern = tree_attn_kernel<STAGES, INFLIGHT, NHE, PFW>;
    constexpr int smem = smem_bytes<STAGES>();
    cudaFuncSetAttribute(kern, cudaFuncAttributeMaxDynamicSharedMemorySize, smem);
    CUtensorMap mk, mv, mvh;
    make_map(&mvh, d_in[2], TILE / 2, promo);
    make_map(&mk, d_in[1], TILE, promo);
    make_map(&mv, d_in[2], TILE, promo);
    kern<<<NHEAD * NSPLIT, NTHREADS, smem, stream>>>((const __nv_bfloat16*)d_in[1], (const __nv_bfloat16*)d_in[0],
                                                     (const __nv_bfloat16*)d_in[3], (const __nv_bfloat16*)d_in[4],
                                                     (const __nv_bfloat16*)d_in[5], (__nv_bfloat16*)d_out, mk, mv, mvh);
}

}

extern "C" void kernel_launch(void* const* d_in, const int* in_sizes, int n_in, void* d_out, int out_size) {
    (void)in_sizes; (void)n_in; (void)out_size;
    ta::launch<5, 4, 6, 6>(d_in, d_out, CU_TENSOR_MAP_L2_PROMOTION_L2_128B, cudaStreamPerThread);
}
```

```cpp
#include <cuda_runtime.h>
#include <cuda_bf16.h>
#include <cuda.h>
#include <stdint.h>

namespace ta {

constexpr int NB = 2, HKV = 16, CTX = 8192, HD = 128;
constexpr int NHEAD = NB * HKV;
constexpr int NSPLIT = 4;
constexpr int KEYS = CTX / NSPLIT;
constexpr int TILE = 128;
constexpr int NT = KEYS / TILE;
constexpr int TB = TILE * HD * 2;
constexpr int STAGES = 6, INFLIGHT = 4, NHE = 6;
constexpr int NF = NT - NHE / 2;
constexpr int NE = NT + NF + NHE;
constexpr int NCW = 8;
constexpr int NTHREADS = (NCW + 2) * 32;
constexpr float LOG2E = 1.4426950408889634f;
constexpr float SCALE = 0.08838834764831845f;
constexpr uint32_t SPIN_LIMIT = 1u << 24;
constexpr uint64_t EVICT_FIRST = 0x12F0000000000000ull;

__device__ unsigned long long g_ml[NHEAD][NSPLIT][NSPLIT][4];

__device__ __forceinline__ uint32_t smem_u32(const void* p) { return (uint32_t)__cvta_generic_to_shared(p); }
__device__ __forceinline__ void mbar_init(uint32_t bar, uint32_t cnt) {
    asm volatile("mbarrier.init.shared::cta.b64 [%0], %1;" ::"r"(bar), "r"(cnt) : "memory");
}
__device__ __forceinline__ void mbar_expect_tx(uint32_t bar, uint32_t bytes) {
    asm volatile("mbarrier.arrive.expect_tx.shared::cta.b64 _, [%0], %1;" ::"r"(bar), "r"(bytes) : "memory");
}
__device__ __forceinline__ void mbar_arrive(uint32_t bar) {
    asm volatile("mbarrier.arrive.shared::cta.b64 _, [%0];" ::"r"(bar) : "memory");
}
__device__ __forceinline__ void mbar_wait(uint32_t bar, uint32_t parity) {
    uint32_t ok, it = 0;
    do {
        asm volatile("{\n\t.reg .pred p;\n\tmbarrier.try_wait.parity.shared::cta.b64 p, [%1], %2;\n\tselp.u32 %0, 1, 0, p;\n\t}"
                     : "=r"(ok) : "r"(bar), "r"(parity) : "memory");
        if (++it > SPIN_LIMIT) __trap();
    } while (!ok);
}
__device__ __forceinline__ bool mbar_test(uint32_t bar, uint32_t parity) {
    uint32_t ok;
    asm volatile("{\n\t.reg .pred p;\n\tmbarrier.test_wait.parity.shared::cta.b64 p, [%1], %2;\n\tselp.u32 %0, 1, 0, p;\n\t}"
                 : "=r"(ok) : "r"(bar), "r"(parity) : "memory");
    return ok != 0;
}
__device__ __forceinline__ void named_sync(int id, int n) { asm volatile("bar.sync %0, %1;" ::"r"(id), "r"(n) : "memory"); }
__device__ __forceinline__ bool elect_one() {
    uint32_t p;
    asm volatile("{\n\t.reg .pred p;\n\telect.sync _|p, 0xffffffff;\n\tselp.u32 %0, 1, 0, p;\n\t}" : "=r"(p));
    return p != 0;
}
__device__ __forceinline__ void ldsm4(uint32_t (&r)[4], uint32_t a) {
    asm volatile("ldmatrix.sync.aligned.m8n8.x4.shared.b16 {%0,%1,%2,%3}, [%4];"
                 : "=r"(r[0]), "=r"(r[1]), "=r"(r[2]), "=r"(r[3]) : "r"(a) : "memory");
}
__device__ __forceinline__ void ldsm4t(uint32_t (&r)[4], uint32_t a) {
    asm volatile("ldmatrix.sync.aligned.m8n8.x4.trans.shared.b16 {%0,%1,%2,%3}, [%4];"
                 : "=r"(r[0]), "=r"(r[1]), "=r"(r[2]), "=r"(r[3]) : "r"(a) : "memory");
}
__device__ __forceinline__ void mma16816(float (&c)[4], const uint32_t (&a)[4], uint32_t b0, uint32_t b1) {
    asm volatile("mma.sync.aligned.m16n8k16.row.col.f32.bf16.bf16.f32 {%0,%1,%2,%3}, {%4,%5,%6,%7}, {%8,%9}, {%0,%1,%2,%3};"
                 : "+f"(c[0]), "+f"(c[1]), "+f"(c[2]), "+f"(c[3])
                 : "r"(a[0]), "r"(a[1]), "r"(a[2]), "r"(a[3]), "r"(b0), "r"(b1));
}
__device__ __forceinline__ unsigned long long ld_acquire(const unsigned long long* p) {
    unsigned long long v;
    asm volatile("ld.acquire.gpu.global.b64 %0, [%1];" : "=l"(v) : "l"(p) : "memory");
    return v;
}
__device__ __forceinline__ void st_relaxed(unsigned long long* p, float x, uint32_t flag) {
    unsigned long long v = ((unsigned long long)flag << 32) | __float_as_uint(x);
    asm volatile("st.relaxed.gpu.global.b64 [%0], %1;" ::"l"(p), "l"(v) : "memory");
}
__device__ __forceinline__ float bf16r(float x) { return __bfloat162float(__float2bfloat16_rn(x)); }
__device__ __forceinline__ float bf_lo(uint32_t x) { return __uint_as_float(x << 16); }
__device__ __forceinline__ float bf_hi(uint32_t x) { return __uint_as_float(x & 0xffff0000u); }
__device__ __forceinline__ uint32_t pack_bf16(float lo, float hi) {
    uint32_t r;
    asm("cvt.rn.bf16x2.f32 %0, %1, %2;" : "=r"(r) : "f"(hi), "f"(lo));
    return r;
}
__device__ __forceinline__ float ex2(float x) {
    float r;
    asm("ex2.approx.ftz.f32 %0, %1;" : "=f"(r) : "f"(x));
    return r;
}

template <int N> struct IC { static constexpr int value = N; };

struct __align__(16) Misc {
    float wgt[2][2];
    float mred[NCW][2];
    float lred[NCW][2];
    unsigned long long full[STAGES];
    unsigned long long empty[STAGES];
    unsigned long long lready;
    unsigned long long wready;
};

constexpr int SMEM_BYTES = STAGES * TB + KEYS * 4 + (int)sizeof(Misc);

__global__ void __launch_bounds__(NTHREADS, 1)
tree_attn_kernel(const __nv_bfloat16* __restrict__ k_cache, const __nv_bfloat16* __restrict__ q,
                 const __nv_bfloat16* __restrict__ k_tree, const __nv_bfloat16* __restrict__ v_tree,
                 const __nv_bfloat16* __restrict__ tree_mask, __nv_bfloat16* __restrict__ out,
                 const __grid_constant__ CUtensorMap map_k, const __grid_constant__ CUtensorMap map_v,
                 const __grid_constant__ CUtensorMap map_vh) {
    extern __shared__ __align__(1024) unsigned char smem[];
    unsigned char* pbuf = smem + STAGES * TB;
    Misc& misc = *reinterpret_cast<Misc*>(smem + STAGES * TB + KEYS * 4);

    const int bh = blockIdx.x / NSPLIT, split = blockIdx.x % NSPLIT;
    const uint32_t ring = smem_u32(smem);
    const uint32_t full0 = smem_u32(&misc.full[0]), empty0 = smem_u32(&misc.empty[0]);
    const int row0 = blockIdx.x * (KEYS / 8);

    auto issue = [&](const CUtensorMap* m, int half_tile, int s, uint32_t bytes) {
        mbar_expect_tx(full0 + 8 * s, bytes);
        asm volatile("cp.async.bulk.tensor.4d.shared::cluster.global.mbarrier::complete_tx::bytes.L2::cache_hint [%0], [%1, {%3, %3, %3, %4}], [%2], %5;"
                     ::"r"(ring + s * TB), "l"(m), "r"(full0 + 8 * s), "r"(0), "r"(row0 + half_tile * (TILE / 16)), "l"(EVICT_FIRST) : "memory");
    };

    asm volatile("prefetch.global.L2 [%0];" ::"l"(reinterpret_cast<const char*>(k_cache) + (size_t)blockIdx.x * (KEYS * HD * 2) + threadIdx.x * 128) : "memory");
    if (threadIdx.x < 32) {
        if (elect_one()) {
#pragma unroll
            for (int s = 0; s < STAGES; s++) mbar_init(full0 + 8 * s, 1);
            asm volatile("fence.mbarrier_init.release.cluster;" ::: "memory");
#pragma unroll
            for (int i = 0; i < INFLIGHT; i++) issue(&map_k, 2 * i, i, TB);
#pragma unroll
            for (int s = 0; s < STAGES; s++) mbar_init(empty0 + 8 * s, NCW);
            mbar_init(smem_u32(&misc.lready), 1);
            mbar_init(smem_u32(&misc.wready), 2);
            asm volatile("prefetch.tensormap [%0];" ::"l"(&map_v) : "memory");
            asm volatile("prefetch.tensormap [%0];" ::"l"(&map_vh) : "memory");
        }
        __syncwarp();
    }

    const int lane = threadIdx.x & 31;
    const int warp = __shfl_sync(0xffffffffu, (int)(threadIdx.x >> 5), 0) - 2;
    if (warp == -2) {
        named_sync(0, NTHREADS);
        const int js = lane < STAGES ? lane : min(lane - STAGES, STAGES - 1);
        const uint32_t mybar = (lane < STAGES ? full0 : empty0) + 8 * js;
        uint32_t par = js < INFLIGHT ? 0 : 1;
        uint32_t spins = 0;
        int s = INFLIGHT % STAGES;
#pragma unroll 1
        for (int i = INFLIGHT; i < NE; i++) {
            uint32_t busy;
            do {
                __nanosleep(30);
                busy = __ballot_sync(0xffffffffu, !mbar_test(mybar, par));
                if (++spins > (SPIN_LIMIT << 5)) __trap();
            } while (__popc(busy & ((1u << STAGES) - 1)) >= INFLIGHT || (busy >> (STAGES + s) & 1));
            if (elect_one()) {
                if (i < NT + NF) issue(i < NT ? &map_k : &map_v, 2 * (i % NT), s, TB);
                else issue(&map_vh, NF + i - NT, s, TB / 2);
            }
            __syncwarp();
            if (js == s) par ^= 1;
            if (++s == STAGES) s = 0;
        }
    } else if (warp == -1) {
        reinterpret_cast<uint32_t*>(out + 2 * bh * HD)[split * 32 + lane] = 0u;
        const uint2 kt = __ldg(reinterpret_cast<const uint2*>(k_tree + bh * HD + lane * 4));
        const uint2 q0 = __ldg(reinterpret_cast<const uint2*>(q + 2 * bh * HD + lane * 4));
        const uint2 q1 = __ldg(reinterpret_cast<const uint2*>(q + (2 * bh + 1) * HD + lane * 4));
        const __nv_bfloat16 mk = __ldg(tree_mask + bh / HKV);
        named_sync(0, NTHREADS);
        asm volatile("fence.acq_rel.gpu;" ::: "memory");
        float st[2];
        const float madd = bf16r(bf16r(1.0f - __bfloat162float(mk)) * -1000000000.0f);
#pragma unroll
        for (int h = 0; h < 2; h++) {
            const uint2 qv = h ? q1 : q0;
            float a = bf_lo(qv.x) * bf_lo(kt.x) + bf_hi(qv.x) * bf_hi(kt.x) + bf_lo(qv.y) * bf_lo(kt.y) + bf_hi(qv.y) * bf_hi(kt.y);
#pragma unroll
            for (int o = 16; o > 0; o >>= 1) a += __shfl_xor_sync(0xffffffffu, a, o);
            st[h] = bf16r(bf16r(bf16r(a) * SCALE) + madd);
        }
        mbar_wait(smem_u32(&misc.lready), 0);
        const int h = lane & 1, peer = lane >> 2;
        float m = misc.mred[0][h], l = misc.lred[0][h];
#pragma unroll
        for (int w = 1; w < NCW; w++) { m = fmaxf(m, misc.mred[w][h]); l += misc.lred[w][h]; }
        float x = (lane & 2) ? l : m;
        if (peer < NSPLIT && peer != split) {
            st_relaxed(&g_ml[bh][peer][split][lane & 3], x, 1);
            unsigned long long* p = &g_ml[bh][split][peer][lane & 3];
            unsigned long long v = ld_acquire(p);
            uint32_t it = 0;
            while ((v >> 32) == 0) {
                __nanosleep(500);
                v = ld_acquire(p);
                if (++it > SPIN_LIMIT) __trap();
            }
            x = __uint_as_float((uint32_t)v);
            st_relaxed(p, 0.f, 0);
        }
        __syncwarp();
        const float s_t = h ? st[1] : st[0];
        float mi[NSPLIT], M = s_t;
#pragma unroll
        for (int i = 0; i < NSPLIT; i++) { mi[i] = __shfl_sync(0xffffffffu, x, 4 * i + h); M = fmaxf(M, mi[i]); }
        const float et = ex2((s_t - M) * LOG2E);
        float L = et;
#pragma unroll
        for (int i = 0; i < NSPLIT; i++) L = fmaf(ex2((mi[i] - M) * LOG2E), __shfl_sync(0xffffffffu, x, 4 * i + 2 + h), L);
        const float inv = 1.0f / L;
        if (lane < 2) {
            misc.wgt[h][0] = ex2((m - M) * LOG2E) * inv;
            misc.wgt[h][1] = et * inv;
            mbar_arrive(smem_u32(&misc.wready));
        }
    } else {
        const int tid = threadIdx.x - 64;
        const int g = lane >> 2, t = lane & 3;
        uint32_t qf[8][2];
        {
            const uint32_t* qp = reinterpret_cast<const uint32_t*>(q + (2 * bh + (g & 1)) * HD) + t;
#pragma unroll
            for (int j = 0; j < 8; j++) { qf[j][0] = __ldg(qp + 8 * j); qf[j][1] = __ldg(qp + 8 * j + 4); }
        }
        const int oh = t & 1, od = 16 * warp + g + 8 * (t >> 1);
        unsigned short vt_raw;
        asm volatile("ld.global.nc.u16 %0, [%1];" : "=h"(vt_raw) : "l"(v_tree + bh * HD + od));
        named_sync(0, NTHREADS);

        int s = 0, ph = 0;
        const uint32_t pb = smem_u32(pbuf);
        float mx = -INFINITY;
        {
            const uint32_t koff = ring + warp * 4096 + ((lane >> 3) & 1) * 2048 + (lane & 7) * 128;
            const uint32_t x = (lane >> 4) ^ (lane & 7);
            uint32_t sp = pb + (warp >> 1) * 128 + (warp & 1) * 8 + oh * 64 + (g >> 1) * 16 + (2 * (t >> 1) + (g & 1)) * 2;
#pragma unroll 1
            for (int i = 0; i < NT; i++) {
                mbar_wait(full0 + 8 * s, ph);
                float c0[4] = {0.f, 0.f, 0.f, 0.f}, c1[4] = {0.f, 0.f, 0.f, 0.f};
                uint32_t a[8][4];
#pragma unroll
                for (int j = 0; j < 8; j++) ldsm4(a[j], koff + s * TB + (j >> 2) * 1024 + (((2 * (j & 3)) ^ x) << 4));
#pragma unroll
                for (int j = 0; j < 8; j += 2) {
                    mma16816(c0, a[j], qf[j][0], qf[j][1]);
                    mma16816(c1, a[j + 1], qf[j + 1][0], qf[j + 1][1]);
                }
                __syncwarp();
                if (lane == 0) mbar_arrive(empty0 + 8 * s);
                const float lo = (t & 1) ? c0[1] + c1[1] : c0[0] + c1[0];
                const float hi = (t & 1) ? c0[3] + c1[3] : c0[2] + c1[2];
                const __nv_bfloat16 sb = __float2bfloat16_rn(bf16r((t & 2) ? hi : lo) * SCALE);
                mx = fmaxf(mx, __bfloat162float(sb));
                asm volatile("st.shared.b16 [%0], %1;" ::"r"(sp), "h"(__bfloat16_as_ushort(sb)) : "memory");
                sp += TILE * 4;
                if (++s == STAGES) { s = 0; ph ^= 1; }
            }
        }
#pragma unroll
        for (int o = 2; o < 32; o <<= 1) mx = fmaxf(mx, __shfl_xor_sync(0xffffffffu, mx, o));
        if (lane < 2) misc.mred[warp][lane] = mx;
        named_sync(1, NCW * 32);
        {
            const int h = (tid >> 2) & 1;
            float m = misc.mred[0][h];
#pragma unroll
            for (int w = 1; w < NCW; w++) m = fmaxf(m, misc.mred[w][h]);
            float l = 0.f;
#pragma unroll
            for (int r = 0; r < KEYS * 4 / 16 / (NCW * 32); r++) {
                uint4* pp = reinterpret_cast<uint4*>(pbuf) + tid + r * NCW * 32;
                uint4 v = *pp;
                uint32_t* u = reinterpret_cast<uint32_t*>(&v);
#pragma unroll
                for (int e = 0; e < 4; e++) {
                    const float p0 = ex2((bf_lo(u[e]) - m) * LOG2E), p1 = ex2((bf_hi(u[e]) - m) * LOG2E);
                    l += p0 + p1;
                    u[e] = pack_bf16(p0, p1);
                }
                *pp = v;
            }
            l += __shfl_xor_sync(0xffffffffu, l, 1);
            l += __shfl_xor_sync(0xffffffffu, l, 2);
            l += __shfl_xor_sync(0xffffffffu, l, 8);
            l += __shfl_xor_sync(0xffffffffu, l, 16);
            if ((lane & ~4) == 0) misc.lred[warp][lane >> 2] = l;
        }
        named_sync(1, NCW * 32);
        if (tid == 0) mbar_arrive(smem_u32(&misc.lready));

        float o0[4] = {0.f, 0.f, 0.f, 0.f}, o1[4] = {0.f, 0.f, 0.f, 0.f};
        const uint32_t voff = ring + (lane >> 4) * 2048 + (warp >> 2) * 1024 + (lane & 7) * 128 +
                              ((((2 * warp + ((lane >> 3) & 1)) & 7) ^ (lane & 7)) << 4);
        uint32_t poff = pb + (g & 1) * 64 + t * 16;
        __nv_bfloat16* optr = out + (2 * bh + oh) * HD + od;
        float w = 0.f, vt = 0.f;
        auto pv = [&](auto nk, bool last) {
            constexpr int NK = decltype(nk)::value;
            uint4 pf[NK];
#pragma unroll
            for (int kp = 0; kp < NK; kp++)
                asm volatile("ld.shared.v4.u32 {%0,%1,%2,%3}, [%4];" : "=r"(pf[kp].x), "=r"(pf[kp].y), "=r"(pf[kp].z), "=r"(pf[kp].w)
                             : "r"(poff + kp * 128));
            poff += NK * 128;
            if (last) {
                mbar_wait(smem_u32(&misc.wready), 0);
                const float2 ww = *reinterpret_cast<const float2*>(&misc.wgt[oh][0]);
                w = ww.x;
                if (split == 0) vt = __bfloat162float(__ushort_as_bfloat16(vt_raw)) * ww.y;
            }
            mbar_wait(full0 + 8 * s, ph);
            uint32_t a[2 * NK][4];
#pragma unroll
            for (int kg = 0; kg < 2 * NK; kg++) ldsm4t(a[kg], voff + s * TB + kg * 4096);
#pragma unroll
            for (int kp = 0; kp < NK; kp++) {
                mma16816(o0, a[2 * kp], pf[kp].x, pf[kp].y);
                mma16816(o1, a[2 * kp + 1], pf[kp].z, pf[kp].w);
            }
            __syncwarp();
            if (lane == 0) mbar_arrive(empty0 + 8 * s);
            if (++s == STAGES) { s = 0; ph ^= 1; }
        };
#pragma unroll 1
        for (int i = 0; i < NF; i++) pv(IC<4>{}, false);
#pragma unroll 1
        for (int i = 0; i < NHE; i++) pv(IC<2>{}, i == NHE - 1);
        const float lo = (t & 1) ? o0[1] + o1[1] : o0[0] + o1[0];
        const float hi = (t & 1) ? o0[3] + o1[3] : o0[2] + o1[2];
        const float own = fmaf(w, (t & 2) ? hi : lo, vt);
        const float nb = __shfl_xor_sync(0xffffffffu, own, 4);
        if (!(g & 1)) asm volatile("red.relaxed.gpu.global.add.noftz.bf16x2 [%0], %1;" ::"l"(optr), "r"(pack_bf16(own, nb)) : "memory");
    }
}

typedef CUresult (*EncodeFn)(CUtensorMap*, CUtensorMapDataType, cuuint32_t, void*, const cuuint64_t*, const cuuint64_t*,
                             const cuuint32_t*, const cuuint32_t*, CUtensorMapInterleave, CUtensorMapSwizzle,
                             CUtensorMapL2promotion, CUtensorMapFloatOOBfill);

static void make_map(CUtensorMap* m, const void* base, int rows) {
    static EncodeFn enc = nullptr;
    if (!enc) {
        cudaDriverEntryPointQueryResult qr;
        cudaGetDriverEntryPoint("cuTensorMapEncodeTiled", (void**)&enc, cudaEnableDefault, &qr);
    }
    cuuint64_t gd[4] = {64, 8, 2, (cuuint64_t)NHEAD * CTX / 8};
    cuuint64_t gs[3] = {256, 128, 2048};
    cuuint32_t bd[4] = {64, 8, 2, (cuuint32_t)rows / 8};
    cuuint32_t es[4] = {1, 1, 1, 1};
    enc(m, CU_TENSOR_MAP_DATA_TYPE_BFLOAT16, 4, const_cast<void*>(base), gd, gs, bd, es, CU_TENSOR_MAP_INTERLEAVE_NONE,
        CU_TENSOR_MAP_SWIZZLE_128B, CU_TENSOR_MAP_L2_PROMOTION_L2_128B, CU_TENSOR_MAP_FLOAT_OOB_FILL_NONE);
}

}

extern "C" void kernel_launch(void* const* d_in, const int* in_sizes, int n_in, void* d_out, int out_size) {
    (void)in_sizes; (void)n_in; (void)out_size;
    using namespace ta;
    cudaFuncSetAttribute(tree_attn_kernel, cudaFuncAttributeMaxDynamicSharedMemorySize, SMEM_BYTES);
    CUtensorMap mk, mv, mvh;
    make_map(&mk, d_in[1], TILE);
    make_map(&mv, d_in[2], TILE);
    make_map(&mvh, d_in[2], TILE / 2);
    tree_attn_kernel<<<NHEAD * NSPLIT, NTHREADS, SMEM_BYTES, cudaStreamPerThread>>>(
        (const __nv_bfloat16*)d_in[1], (const __nv_bfloat16*)d_in[0], (const __nv_bfloat16*)d_in[3],
        (const __nv_bfloat16*)d_in[4], (const __nv_bfloat16*)d_in[5], (__nv_bfloat16*)d_out, mk, mv, mvh);
}
```

```cpp
#include <cuda_runtime.h>
#include <cuda_bf16.h>
#include <cuda.h>
#include <stdint.h>

namespace ta {

constexpr int NB = 2, HKV = 16, CTX = 8192, HD = 128;
constexpr int NHEAD = NB * HKV;
constexpr int NSPLIT = 4;
constexpr int KEYS = CTX / NSPLIT;
constexpr int TILE = 128;
constexpr int NT = KEYS / TILE;
constexpr int TB = TILE * HD * 2;
constexpr int STAGES = 6, INFLIGHT = 4, NHE = 6;
constexpr int NF = NT - NHE / 2;
constexpr int NE = NT + NF + NHE;
constexpr int NCW = 8;
constexpr int NTHREADS = (NCW + 2) * 32;
constexpr float LOG2E = 1.4426950408889634f;
constexpr float SCALE = 0.08838834764831845f;
constexpr uint32_t SPIN_LIMIT = 1u << 24;

__device__ unsigned long long g_ml[NHEAD][NSPLIT][NSPLIT][4];

__device__ __forceinline__ uint32_t smem_u32(const void* p) { return (uint32_t)__cvta_generic_to_shared(p); }
__device__ __forceinline__ void mbar_init(uint32_t bar, uint32_t cnt) {
    asm volatile("mbarrier.init.shared::cta.b64 [%0], %1;" ::"r"(bar), "r"(cnt) : "memory");
}
__device__ __forceinline__ void mbar_expect_tx(uint32_t bar, uint32_t bytes) {
    asm volatile("mbarrier.arrive.expect_tx.shared::cta.b64 _, [%0], %1;" ::"r"(bar), "r"(bytes) : "memory");
}
__device__ __forceinline__ void mbar_arrive(uint32_t bar) {
    asm volatile("mbarrier.arrive.shared::cta.b64 _, [%0];" ::"r"(bar) : "memory");
}
__device__ __forceinline__ void mbar_wait(uint32_t bar, uint32_t parity) {
    uint32_t ok, it = 0;
    do {
        asm volatile("{\n\t.reg .pred p;\n\tmbarrier.try_wait.parity.shared::cta.b64 p, [%1], %2;\n\tselp.u32 %0, 1, 0, p;\n\t}"
                     : "=r"(ok) : "r"(bar), "r"(parity) : "memory");
        if (++it > SPIN_LIMIT) __trap();
    } while (!ok);
}
__device__ __forceinline__ bool mbar_test(uint32_t bar, uint32_t parity) {
    uint32_t ok;
    asm volatile("{\n\t.reg .pred p;\n\tmbarrier.test_wait.parity.shared::cta.b64 p, [%1], %2;\n\tselp.u32 %0, 1, 0, p;\n\t}"
                 : "=r"(ok) : "r"(bar), "r"(parity) : "memory");
    return ok != 0;
}
__device__ __forceinline__ void named_sync(int id, int n) { asm volatile("bar.sync %0, %1;" ::"r"(id), "r"(n) : "memory"); }
__device__ __forceinline__ bool elect_one() {
    uint32_t p;
    asm volatile("{\n\t.reg .pred p;\n\telect.sync _|p, 0xffffffff;\n\tselp.u32 %0, 1, 0, p;\n\t}" : "=r"(p));
    return p != 0;
}
__device__ __forceinline__ void ldsm4(uint32_t (&r)[4], uint32_t a) {
    asm volatile("ldmatrix.sync.aligned.m8n8.x4.shared.b16 {%0,%1,%2,%3}, [%4];"
                 : "=r"(r[0]), "=r"(r[1]), "=r"(r[2]), "=r"(r[3]) : "r"(a) : "memory");
}
__device__ __forceinline__ void ldsm4t(uint32_t (&r)[4], uint32_t a) {
    asm volatile("ldmatrix.sync.aligned.m8n8.x4.trans.shared.b16 {%0,%1,%2,%3}, [%4];"
                 : "=r"(r[0]), "=r"(r[1]), "=r"(r[2]), "=r"(r[3]) : "r"(a) : "memory");
}
__device__ __forceinline__ void mma16816(float (&c)[4], const uint32_t (&a)[4], uint32_t b0, uint32_t b1) {
    asm volatile("mma.sync.aligned.m16n8k16.row.col.f32.bf16.bf16.f32 {%0,%1,%2,%3}, {%4,%5,%6,%7}, {%8,%9}, {%0,%1,%2,%3};"
                 : "+f"(c[0]), "+f"(c[1]), "+f"(c[2]), "+f"(c[3])
                 : "r"(a[0]), "r"(a[1]), "r"(a[2]), "r"(a[3]), "r"(b0), "r"(b1));
}
__device__ __forceinline__ unsigned long long ld_acquire(const unsigned long long* p) {
    unsigned long long v;
    asm volatile("ld.acquire.gpu.global.b64 %0, [%1];" : "=l"(v) : "l"(p) : "memory");
    return v;
}
__device__ __forceinline__ void st_relaxed(unsigned long long* p, float x, uint32_t flag) {
    unsigned long long v = ((unsigned long long)flag << 32) | __float_as_uint(x);
    asm volatile("st.relaxed.gpu.global.b64 [%0], %1;" ::"l"(p), "l"(v) : "memory");
}
__device__ __forceinline__ float bf16r(float x) { return __bfloat162float(__float2bfloat16_rn(x)); }
__device__ __forceinline__ float bf_lo(uint32_t x) { return __uint_as_float(x << 16); }
__device__ __forceinline__ float bf_hi(uint32_t x) { return __uint_as_float(x & 0xffff0000u); }
__device__ __forceinline__ uint32_t pack_bf16(float lo, float hi) {
    uint32_t r;
    asm("cvt.rn.bf16x2.f32 %0, %1, %2;" : "=r"(r) : "f"(hi), "f"(lo));
    return r;
}
__device__ __forceinline__ float ex2(float x) {
    float r;
    asm("ex2.approx.ftz.f32 %0, %1;" : "=f"(r) : "f"(x));
    return r;
}

template <int N> struct IC { static constexpr int value = N; };

struct __align__(16) Misc {
    float wgt[2][2];
    float mred[NCW][2];
    float lred[NCW][2];
    unsigned long long full[STAGES];
    unsigned long long empty[STAGES];
    unsigned long long lready;
    unsigned long long wready;
};

constexpr int SMEM_BYTES = STAGES * TB + KEYS * 4 + (int)sizeof(Misc);

__global__ void __launch_bounds__(NTHREADS, 1)
tree_attn_kernel(const __nv_bfloat16* __restrict__ k_cache, const __nv_bfloat16* __restrict__ q,
                 const __nv_bfloat16* __restrict__ k_tree, const __nv_bfloat16* __restrict__ v_tree,
                 const __nv_bfloat16* __restrict__ tree_mask, __nv_bfloat16* __restrict__ out,
                 const __grid_constant__ CUtensorMap map_k, const __grid_constant__ CUtensorMap map_v,
                 const __grid_constant__ CUtensorMap map_vh) {
    extern __shared__ __align__(1024) unsigned char smem[];
    unsigned char* pbuf = smem + STAGES * TB;
    Misc& misc = *reinterpret_cast<Misc*>(smem + STAGES * TB + KEYS * 4);

    const int bh = blockIdx.x / NSPLIT, split = blockIdx.x % NSPLIT;
    const uint32_t ring = smem_u32(smem);
    const uint32_t full0 = smem_u32(&misc.full[0]), empty0 = smem_u32(&misc.empty[0]);
    const int row0 = blockIdx.x * (KEYS / 8);
#define ROTV ((4 * (bh >> 1)) % NT)
    const int rotv = ROTV;

    auto issue = [&](const CUtensorMap* m, int half_tile, int s, uint32_t bytes) {
        mbar_expect_tx(full0 + 8 * s, bytes);
        uint64_t pol;
        asm("createpolicy.fractional.L2::evict_first.b64 %0, 1.0;" : "=l"(pol));
        asm volatile("cp.async.bulk.tensor.4d.shared::cluster.global.mbarrier::complete_tx::bytes.L2::cache_hint [%0], [%1, {%3, %3, %3, %4}], [%2], %5;"
                     ::"r"(ring + s * TB), "l"(m), "r"(full0 + 8 * s), "r"(0), "r"(row0 + half_tile * (TILE / 16)), "l"(pol) : "memory");
    };

    asm volatile("prefetch.global.L2 [%0];" ::"l"(reinterpret_cast<const char*>(k_cache) + (size_t)blockIdx.x * (KEYS * HD * 2) + threadIdx.x * 128) : "memory");
    if (threadIdx.x < 32) {
        if (elect_one()) {
#pragma unroll
            for (int s = 0; s < STAGES; s++) mbar_init(full0 + 8 * s, 1);
            asm volatile("fence.mbarrier_init.release.cluster;" ::: "memory");
#pragma unroll
            for (int i = 0; i < INFLIGHT; i++) issue(&map_k, 2 * i, i, TB);
#pragma unroll
            for (int s = 0; s < STAGES; s++) mbar_init(empty0 + 8 * s, NCW);
            mbar_init(smem_u32(&misc.lready), 1);
            mbar_init(smem_u32(&misc.wready), 2);
            asm volatile("prefetch.tensormap [%0];" ::"l"(&map_v) : "memory");
            asm volatile("prefetch.tensormap [%0];" ::"l"(&map_vh) : "memory");
        }
        __syncwarp();
    }

    const int lane = threadIdx.x & 31;
    const int warp = __shfl_sync(0xffffffffu, (int)(threadIdx.x >> 5), 0) - 2;
    if (warp == -2) {
        named_sync(0, NTHREADS);
        const int js = lane < STAGES ? lane : min(lane - STAGES, STAGES - 1);
        const uint32_t mybar = (lane < STAGES ? full0 : empty0) + 8 * js;
        uint32_t par = js < INFLIGHT ? 0 : 1;
        uint32_t spins = 0;
        int s = INFLIGHT % STAGES;
#pragma unroll 1
        for (int i = INFLIGHT; i < NE; i++) {
            uint32_t busy;
            do {
                __nanosleep(30);
                busy = __ballot_sync(0xffffffffu, !mbar_test(mybar, par));
                if (++spins > (SPIN_LIMIT << 5)) __trap();
            } while (__popc(busy & ((1u << STAGES) - 1)) >= INFLIGHT || (busy >> (STAGES + s) & 1));
            if (elect_one()) {
                if (i < NT) issue(&map_k, 2 * i, s, TB);
                else if (i < NT + NF) issue(&map_v, 2 * ((i + rotv) % NT), s, TB);
                else issue(&map_vh, (2 * rotv + NF + i - NT) % (2 * NT), s, TB / 2);
            }
            __syncwarp();
            if (js == s) par ^= 1;
            if (++s == STAGES) s = 0;
        }
    } else if (warp == -1) {
        reinterpret_cast<uint32_t*>(out + 2 * bh * HD)[split * 32 + lane] = 0u;
        const uint2 kt = __ldg(reinterpret_cast<const uint2*>(k_tree + bh * HD + lane * 4));
        const uint2 q0 = __ldg(reinterpret_cast<const uint2*>(q + 2 * bh * HD + lane * 4));
        const uint2 q1 = __ldg(reinterpret_cast<const uint2*>(q + (2 * bh + 1) * HD + lane * 4));
        const __nv_bfloat16 mk = __ldg(tree_mask + bh / HKV);
        named_sync(0, NTHREADS);
        asm volatile("fence.acq_rel.gpu;" ::: "memory");
        float st[2];
        const float madd = bf16r(bf16r(1.0f - __bfloat162float(mk)) * -1000000000.0f);
#pragma unroll
        for (int h = 0; h < 2; h++) {
            const uint2 qv = h ? q1 : q0;
            float a = bf_lo(qv.x) * bf_lo(kt.x) + bf_hi(qv.x) * bf_hi(kt.x) + bf_lo(qv.y) * bf_lo(kt.y) + bf_hi(qv.y) * bf_hi(kt.y);
#pragma unroll
            for (int o = 16; o > 0; o >>= 1) a += __shfl_xor_sync(0xffffffffu, a, o);
            st[h] = bf16r(bf16r(bf16r(a) * SCALE) + madd);
        }
        mbar_wait(smem_u32(&misc.lready), 0);
        const int h = lane & 1, peer = lane >> 2;
        float m = misc.mred[0][h], l = misc.lred[0][h];
#pragma unroll
        for (int w = 1; w < NCW; w++) { m = fmaxf(m, misc.mred[w][h]); l += misc.lred[w][h]; }
        float x = (lane & 2) ? l : m;
        if (peer < NSPLIT && peer != split) {
            st_relaxed(&g_ml[bh][peer][split][lane & 3], x, 1);
            unsigned long long* p = &g_ml[bh][split][peer][lane & 3];
            unsigned long long v = ld_acquire(p);
            uint32_t it = 0;
            while ((v >> 32) == 0) {
                __nanosleep(500);
                v = ld_acquire(p);
                if (++it > SPIN_LIMIT) __trap();
            }
            x = __uint_as_float((uint32_t)v);
            st_relaxed(p, 0.f, 0);
        }
        __syncwarp();
        const float s_t = h ? st[1] : st[0];
        float mi[NSPLIT], M = s_t;
#pragma unroll
        for (int i = 0; i < NSPLIT; i++) { mi[i] = __shfl_sync(0xffffffffu, x, 4 * i + h); M = fmaxf(M, mi[i]); }
        const float et = ex2((s_t - M) * LOG2E);
        float L = et;
#pragma unroll
        for (int i = 0; i < NSPLIT; i++) L = fmaf(ex2((mi[i] - M) * LOG2E), __shfl_sync(0xffffffffu, x, 4 * i + 2 + h), L);
        const float inv = 1.0f / L;
        if (lane < 2) {
            misc.wgt[h][0] = ex2((m - M) * LOG2E) * inv;
            misc.wgt[h][1] = et * inv;
            mbar_arrive(smem_u32(&misc.wready));
        }
    } else {
        const int tid = threadIdx.x - 64;
        const int g = lane >> 2, t = lane & 3;
        uint32_t qf[8][2];
        {
            const uint32_t* qp = reinterpret_cast<const uint32_t*>(q + (2 * bh + (g & 1)) * HD) + t;
#pragma unroll
            for (int j = 0; j < 8; j++) { qf[j][0] = __ldg(qp + 8 * j); qf[j][1] = __ldg(qp + 8 * j + 4); }
        }
        const int oh = t & 1, od = 16 * warp + g + 8 * (t >> 1);
        unsigned short vt_raw;
        asm volatile("ld.global.nc.u16 %0, [%1];" : "=h"(vt_raw) : "l"(v_tree + bh * HD + od));
        named_sync(0, NTHREADS);

        int s = 0, ph = 0;
        const uint32_t pb = smem_u32(pbuf);
        float mx = -INFINITY;
        {
            const uint32_t koff = ring + warp * 4096 + ((lane >> 3) & 1) * 2048 + (lane & 7) * 128;
            const uint32_t x = (lane >> 4) ^ (lane & 7);
            uint32_t sp = pb + (warp >> 1) * 128 + (warp & 1) * 8 + oh * 64 + (g >> 1) * 16 + (2 * (t >> 1) + (g & 1)) * 2;
#pragma unroll 1
            for (int i = 0; i < NT; i++) {
                mbar_wait(full0 + 8 * s, ph);
                float c0[4] = {0.f, 0.f, 0.f, 0.f}, c1[4] = {0.f, 0.f, 0.f, 0.f};
                uint32_t a[8][4];
#pragma unroll
                for (int j = 0; j < 8; j++) ldsm4(a[j], koff + s * TB + (j >> 2) * 1024 + (((2 * (j & 3)) ^ x) << 4));
#pragma unroll
                for (int j = 0; j < 8; j += 2) {
                    mma16816(c0, a[j], qf[j][0], qf[j][1]);
                    mma16816(c1, a[j + 1], qf[j + 1][0], qf[j + 1][1]);
                }
                __syncwarp();
                if (lane == 0) mbar_arrive(empty0 + 8 * s);
                const float lo = (t & 1) ? c0[1] + c1[1] : c0[0] + c1[0];
                const float hi = (t & 1) ? c0[3] + c1[3] : c0[2] + c1[2];
                const __nv_bfloat16 sb = __float2bfloat16_rn(bf16r((t & 2) ? hi : lo) * SCALE);
                mx = fmaxf(mx, __bfloat162float(sb));
                asm volatile("st.shared.b16 [%0], %1;" ::"r"(sp), "h"(__bfloat16_as_ushort(sb)) : "memory");
                sp += TILE * 4;
                if (++s == STAGES) { s = 0; ph ^= 1; }
            }
        }
#pragma unroll
        for (int o = 2; o < 32; o <<= 1) mx = fmaxf(mx, __shfl_xor_sync(0xffffffffu, mx, o));
        if (lane < 2) misc.mred[warp][lane] = mx;
        named_sync(1, NCW * 32);
        {
            const int h = (tid >> 2) & 1;
            float m = misc.mred[0][h];
#pragma unroll
            for (int w = 1; w < NCW; w++) m = fmaxf(m, misc.mred[w][h]);
            float l = 0.f;
#pragma unroll
            for (int r = 0; r < KEYS * 4 / 16 / (NCW * 32); r++) {
                uint4* pp = reinterpret_cast<uint4*>(pbuf) + tid + r * NCW * 32;
                uint4 v = *pp;
                uint32_t* u = reinterpret_cast<uint32_t*>(&v);
#pragma unroll
                for (int e = 0; e < 4; e++) {
                    const float p0 = ex2((bf_lo(u[e]) - m) * LOG2E), p1 = ex2((bf_hi(u[e]) - m) * LOG2E);
                    l += p0 + p1;
                    u[e] = pack_bf16(p0, p1);
                }
                *pp = v;
            }
            l += __shfl_xor_sync(0xffffffffu, l, 1);
            l += __shfl_xor_sync(0xffffffffu, l, 2);
            l += __shfl_xor_sync(0xffffffffu, l, 8);
            l += __shfl_xor_sync(0xffffffffu, l, 16);
            if ((lane & ~4) == 0) misc.lred[warp][lane >> 2] = l;
        }
        named_sync(1, NCW * 32);
        if (tid == 0) mbar_arrive(smem_u32(&misc.lready));

        float o0[4] = {0.f, 0.f, 0.f, 0.f}, o1[4] = {0.f, 0.f, 0.f, 0.f};
        const uint32_t voff = ring + (lane >> 4) * 2048 + (warp >> 2) * 1024 + (lane & 7) * 128 +
                              ((((2 * warp + ((lane >> 3) & 1)) & 7) ^ (lane & 7)) << 4);
        const uint32_t pbase = pb + (g & 1) * 64 + t * 16;
        uint32_t poff = rotv * (TILE * 4);
        __nv_bfloat16* optr = out + (2 * bh + oh) * HD + od;
        float w = 0.f, vt = 0.f;
        auto pv = [&](auto nk, bool last) {
            constexpr int NK = decltype(nk)::value;
            uint4 pf[NK];
#pragma unroll
            for (int kp = 0; kp < NK; kp++)
                asm volatile("ld.shared.v4.u32 {%0,%1,%2,%3}, [%4];" : "=r"(pf[kp].x), "=r"(pf[kp].y), "=r"(pf[kp].z), "=r"(pf[kp].w)
                             : "r"(pbase + poff + kp * 128));
            poff = (poff + NK * 128) % (KEYS * 4);
            if (last) {
                mbar_wait(smem_u32(&misc.wready), 0);
                const float2 ww = *reinterpret_cast<const float2*>(&misc.wgt[oh][0]);
                w = ww.x;
                if (split == 0) vt = __bfloat162float(__ushort_as_bfloat16(vt_raw)) * ww.y;
            }
            mbar_wait(full0 + 8 * s, ph);
            uint32_t a[2 * NK][4];
#pragma unroll
            for (int kg = 0; kg < 2 * NK; kg++) ldsm4t(a[kg], voff + s * TB + kg * 4096);
#pragma unroll
            for (int kp = 0; kp < NK; kp++) {
                mma16816(o0, a[2 * kp], pf[kp].x, pf[kp].y);
                mma16816(o1, a[2 * kp + 1], pf[kp].z, pf[kp].w);
            }
            __syncwarp();
            if (lane == 0) mbar_arrive(empty0 + 8 * s);
            if (++s == STAGES) { s = 0; ph ^= 1; }
        };
#pragma unroll 1
        for (int i = 0; i < NF; i++) pv(IC<4>{}, false);
#pragma unroll 1
        for (int i = 0; i < NHE; i++) pv(IC<2>{}, i == NHE - 1);
        const float lo = (t & 1) ? o0[1] + o1[1] : o0[0] + o1[0];
        const float hi = (t & 1) ? o0[3] + o1[3] : o0[2] + o1[2];
        const float own = fmaf(w, (t & 2) ? hi : lo, vt);
        const float nb = __shfl_xor_sync(0xffffffffu, own, 4);
        if (!(g & 1)) asm volatile("red.relaxed.gpu.global.add.noftz.bf16x2 [%0], %1;" ::"l"(optr), "r"(pack_bf16(own, nb)) : "memory");
    }
}

typedef CUresult (*EncodeFn)(CUtensorMap*, CUtensorMapDataType, cuuint32_t, void*, const cuuint64_t*, const cuuint64_t*,
                             const cuuint32_t*, const cuuint32_t*, CUtensorMapInterleave, CUtensorMapSwizzle,
                             CUtensorMapL2promotion, CUtensorMapFloatOOBfill);

static void make_map(CUtensorMap* m, const void* base, int rows) {
    static EncodeFn enc = nullptr;
    if (!enc) {
        cudaDriverEntryPointQueryResult qr;
        cudaGetDriverEntryPoint("cuTensorMapEncodeTiled", (void**)&enc, cudaEnableDefault, &qr);
    }
    cuuint64_t gd[4] = {64, 8, 2, (cuuint64_t)NHEAD * CTX / 8};
    cuuint64_t gs[3] = {256, 128, 2048};
    cuuint32_t bd[4] = {64, 8, 2, (cuuint32_t)rows / 8};
    cuuint32_t es[4] = {1, 1, 1, 1};
    enc(m, CU_TENSOR_MAP_DATA_TYPE_BFLOAT16, 4, const_cast<void*>(base), gd, gs, bd, es, CU_TENSOR_MAP_INTERLEAVE_NONE,
        CU_TENSOR_MAP_SWIZZLE_128B, CU_TENSOR_MAP_L2_PROMOTION_L2_128B, CU_TENSOR_MAP_FLOAT_OOB_FILL_NONE);
}

}

extern "C" void kernel_launch(void* const* d_in, const int* in_sizes, int n_in, void* d_out, int out_size) {
    (void)in_sizes; (void)n_in; (void)out_size;
    using namespace ta;
    cudaFuncSetAttribute(tree_attn_kernel, cudaFuncAttributeMaxDynamicSharedMemorySize, SMEM_BYTES);
    CUtensorMap mk, mv, mvh;
    make_map(&mk, d_in[1], TILE);
    make_map(&mv, d_in[2], TILE);
    make_map(&mvh, d_in[2], TILE / 2);
    tree_attn_kernel<<<NHEAD * NSPLIT, NTHREADS, SMEM_BYTES, cudaStreamPerThread>>>(
        (const __nv_bfloat16*)d_in[1], (const __nv_bfloat16*)d_in[0], (const __nv_bfloat16*)d_in[3],
        (const __nv_bfloat16*)d_in[4], (const __nv_bfloat16*)d_in[5], (__nv_bfloat16*)d_out, mk, mv, mvh);
}
```

```cpp
#include <cuda_runtime.h>
#include <cuda_bf16.h>
#include <cuda.h>
#include <stdint.h>

namespace ta {

constexpr int NB = 2, HKV = 16, CTX = 8192, HD = 128;
constexpr int NHEAD = NB * HKV;
constexpr int NSPLIT = 4;
constexpr int KEYS = CTX / NSPLIT;
constexpr int TILE = 128;
constexpr int NT = KEYS / TILE;
constexpr int TB = TILE * HD * 2;
constexpr int STAGES = 6, INFLIGHT = 4, NHE = 6;
constexpr int NF = NT - NHE / 2;
constexpr int NE = NT + NF + NHE;
constexpr int NCW = 8;
constexpr int NTHREADS = (NCW + 2) * 32;
constexpr float LOG2E = 1.4426950408889634f;
constexpr float SCALE = 0.08838834764831845f;
constexpr uint32_t SPIN_LIMIT = 1u << 21;

__device__ unsigned long long g_ml[NHEAD][NSPLIT][NSPLIT][4];

__device__ __forceinline__ uint32_t smem_u32(const void* p) { return (uint32_t)__cvta_generic_to_shared(p); }
__device__ __forceinline__ void mbar_init(uint32_t bar, uint32_t cnt) {
    asm volatile("mbarrier.init.shared::cta.b64 [%0], %1;" ::"r"(bar), "r"(cnt) : "memory");
}
__device__ __forceinline__ void mbar_expect_tx(uint32_t bar, uint32_t bytes) {
    asm volatile("mbarrier.arrive.expect_tx.shared::cta.b64 _, [%0], %1;" ::"r"(bar), "r"(bytes) : "memory");
}
__device__ __forceinline__ void mbar_arrive(uint32_t bar) {
    asm volatile("mbarrier.arrive.shared::cta.b64 _, [%0];" ::"r"(bar) : "memory");
}
__device__ __forceinline__ void mbar_wait(uint32_t bar, uint32_t parity) {
    uint32_t ok, it = 0;
    do {
        asm volatile("{\n\t.reg .pred p;\n\tmbarrier.try_wait.parity.shared::cta.b64 p, [%1], %2;\n\tselp.u32 %0, 1, 0, p;\n\t}"
                     : "=r"(ok) : "r"(bar), "r"(parity) : "memory");
        if (++it > SPIN_LIMIT) __trap();
    } while (!ok);
}
__device__ __forceinline__ bool mbar_test(uint32_t bar, uint32_t parity) {
    uint32_t ok;
    asm volatile("{\n\t.reg .pred p;\n\tmbarrier.test_wait.parity.shared::cta.b64 p, [%1], %2;\n\tselp.u32 %0, 1, 0, p;\n\t}"
                 : "=r"(ok) : "r"(bar), "r"(parity) : "memory");
    return ok != 0;
}
__device__ __forceinline__ void named_sync(int id, int n) { asm volatile("bar.sync %0, %1;" ::"r"(id), "r"(n) : "memory"); }
__device__ __forceinline__ bool elect_one() {
    uint32_t p;
    asm volatile("{\n\t.reg .pred p;\n\telect.sync _|p, 0xffffffff;\n\tselp.u32 %0, 1, 0, p;\n\t}" : "=r"(p));
    return p != 0;
}
__device__ __forceinline__ void ldsm4(uint32_t (&r)[4], uint32_t a) {
    asm volatile("ldmatrix.sync.aligned.m8n8.x4.shared.b16 {%0,%1,%2,%3}, [%4];"
                 : "=r"(r[0]), "=r"(r[1]), "=r"(r[2]), "=r"(r[3]) : "r"(a) : "memory");
}
__device__ __forceinline__ void ldsm4t(uint32_t (&r)[4], uint32_t a) {
    asm volatile("ldmatrix.sync.aligned.m8n8.x4.trans.shared.b16 {%0,%1,%2,%3}, [%4];"
                 : "=r"(r[0]), "=r"(r[1]), "=r"(r[2]), "=r"(r[3]) : "r"(a) : "memory");
}
__device__ __forceinline__ void mma16816(float (&c)[4], const uint32_t (&a)[4], uint32_t b0, uint32_t b1) {
    asm volatile("mma.sync.aligned.m16n8k16.row.col.f32.bf16.bf16.f32 {%0,%1,%2,%3}, {%4,%5,%6,%7}, {%8,%9}, {%0,%1,%2,%3};"
                 : "+f"(c[0]), "+f"(c[1]), "+f"(c[2]), "+f"(c[3])
                 : "r"(a[0]), "r"(a[1]), "r"(a[2]), "r"(a[3]), "r"(b0), "r"(b1));
}
__device__ __forceinline__ unsigned long long ld_acquire(const unsigned long long* p) {
    unsigned long long v;
    asm volatile("ld.acquire.gpu.global.b64 %0, [%1];" : "=l"(v) : "l"(p) : "memory");
    return v;
}
__device__ __forceinline__ void st_relaxed(unsigned long long* p, float x, uint32_t flag) {
    unsigned long long v = ((unsigned long long)flag << 32) | __float_as_uint(x);
    asm volatile("st.relaxed.gpu.global.b64 [%0], %1;" ::"l"(p), "l"(v) : "memory");
}
__device__ __forceinline__ float bf16r(float x) { return __bfloat162float(__float2bfloat16_rn(x)); }
__device__ __forceinline__ float bf_lo(uint32_t x) { return __uint_as_float(x << 16); }
__device__ __forceinline__ float bf_hi(uint32_t x) { return __uint_as_float(x & 0xffff0000u); }
__device__ __forceinline__ uint32_t pack_bf16(float lo, float hi) {
    uint32_t r;
    asm("cvt.rn.bf16x2.f32 %0, %1, %2;" : "=r"(r) : "f"(hi), "f"(lo));
    return r;
}
__device__ __forceinline__ float ex2(float x) {
    float r;
    asm("ex2.approx.ftz.f32 %0, %1;" : "=f"(r) : "f"(x));
    return r;
}

template <int N> struct IC { static constexpr int value = N; };

struct __align__(16) Misc {
    float wgt[2][2];
    float mred[NCW][2];
    float lred[NCW][2];
    unsigned long long full[STAGES];
    unsigned long long empty[STAGES];
    unsigned long long lready;
    unsigned long long wready;
};

constexpr int SMEM_BYTES = STAGES * TB + KEYS * 4 + (int)sizeof(Misc);

__global__ void __launch_bounds__(NTHREADS, 1)
tree_attn_kernel(const __nv_bfloat16* __restrict__ k_cache, const __nv_bfloat16* __restrict__ q,
                 const __nv_bfloat16* __restrict__ k_tree, const __nv_bfloat16* __restrict__ v_tree,
                 const __nv_bfloat16* __restrict__ tree_mask, __nv_bfloat16* __restrict__ out,
                 const __grid_constant__ CUtensorMap map_k, const __grid_constant__ CUtensorMap map_v,
                 const __grid_constant__ CUtensorMap map_vh) {
    extern __shared__ __align__(1024) unsigned char smem[];
    unsigned char* pbuf = smem + STAGES * TB;
    Misc& misc = *reinterpret_cast<Misc*>(smem + STAGES * TB + KEYS * 4);

    const int bh = blockIdx.x / NSPLIT, split = blockIdx.x % NSPLIT;
    const uint32_t ring = smem_u32(smem);
    const uint32_t full0 = smem_u32(&misc.full[0]), empty0 = smem_u32(&misc.empty[0]);
    const int row0 = blockIdx.x * (KEYS / 8);
    const int rotv = bh % NT;

    auto issue = [&](const CUtensorMap* m, int half_tile, int s, uint32_t bytes) {
        mbar_expect_tx(full0 + 8 * s, bytes);
        uint64_t pol;
        asm("createpolicy.fractional.L2::evict_first.b64 %0, 1.0;" : "=l"(pol));
        asm volatile("cp.async.bulk.tensor.4d.shared::cluster.global.mbarrier::complete_tx::bytes.L2::cache_hint [%0], [%1, {%3, %3, %3, %4}], [%2], %5;"
                     ::"r"(ring + s * TB), "l"(m), "r"(full0 + 8 * s), "r"(0), "r"(row0 + half_tile * (TILE / 16)), "l"(pol) : "memory");
    };

    asm volatile("prefetch.global.L2 [%0];" ::"l"(reinterpret_cast<const char*>(k_cache) + (size_t)blockIdx.x * (KEYS * HD * 2) + threadIdx.x * 128) : "memory");
    if (threadIdx.x < 32) {
        if (elect_one()) {
#pragma unroll
            for (int s = 0; s < STAGES; s++) mbar_init(full0 + 8 * s, 1);
            asm volatile("fence.mbarrier_init.release.cluster;" ::: "memory");
#pragma unroll
            for (int i = 0; i < INFLIGHT; i++) issue(&map_k, 2 * i, i, TB);
#pragma unroll
            for (int s = 0; s < STAGES; s++) mbar_init(empty0 + 8 * s, NCW);
            mbar_init(smem_u32(&misc.lready), 1);
            mbar_init(smem_u32(&misc.wready), 2);
            asm volatile("prefetch.tensormap [%0];" ::"l"(&map_v) : "memory");
            asm volatile("prefetch.tensormap [%0];" ::"l"(&map_vh) : "memory");
        }
        __syncwarp();
    }

    const int lane = threadIdx.x & 31;
    const int warp = __shfl_sync(0xffffffffu, (int)(threadIdx.x >> 5), 0) - 2;
    if (warp == -2) {
        named_sync(0, NTHREADS);
        const int js = lane < STAGES ? lane : min(lane - STAGES, STAGES - 1);
        const uint32_t mybar = (lane < STAGES ? full0 : empty0) + 8 * js;
        uint32_t par = js < INFLIGHT ? 0 : 1;
        uint32_t spins = 0;
        int s = INFLIGHT % STAGES;
#pragma unroll 1
        for (int i = INFLIGHT; i < NE; i++) {
            uint32_t busy;
            do {
                __nanosleep(30);
                busy = __ballot_sync(0xffffffffu, !mbar_test(mybar, par));
                if (++spins > (SPIN_LIMIT << 5)) __trap();
            } while (__popc(busy & ((1u << STAGES) - 1)) >= INFLIGHT || (busy >> (STAGES + s) & 1));
            if (elect_one()) {
                if (i < NT) issue(&map_k, 2 * i, s, TB);
                else if (i < NT + NF) issue(&map_v, 2 * ((i + rotv) % NT), s, TB);
                else issue(&map_vh, (2 * rotv + NF + i - NT) % (2 * NT), s, TB / 2);
            }
            __syncwarp();
            if (js == s) par ^= 1;
            if (++s == STAGES) s = 0;
        }
    } else if (warp == -1) {
        reinterpret_cast<uint32_t*>(out + 2 * bh * HD)[split * 32 + lane] = 0u;
        const uint2 kt = __ldg(reinterpret_cast<const uint2*>(k_tree + bh * HD + lane * 4));
        const uint2 q0 = __ldg(reinterpret_cast<const uint2*>(q + 2 * bh * HD + lane * 4));
        const uint2 q1 = __ldg(reinterpret_cast<const uint2*>(q + (2 * bh + 1) * HD + lane * 4));
        const __nv_bfloat16 mk = __ldg(tree_mask + bh / HKV);
        named_sync(0, NTHREADS);
        asm volatile("fence.acq_rel.gpu;" ::: "memory");
        float st[2];
        const float madd = bf16r(bf16r(1.0f - __bfloat162float(mk)) * -1000000000.0f);
#pragma unroll
        for (int h = 0; h < 2; h++) {
            const uint2 qv = h ? q1 : q0;
            float a = bf_lo(qv.x) * bf_lo(kt.x) + bf_hi(qv.x) * bf_hi(kt.x) + bf_lo(qv.y) * bf_lo(kt.y) + bf_hi(qv.y) * bf_hi(kt.y);
#pragma unroll
            for (int o = 16; o > 0; o >>= 1) a += __shfl_xor_sync(0xffffffffu, a, o);
            st[h] = bf16r(bf16r(bf16r(a) * SCALE) + madd);
        }
        mbar_wait(smem_u32(&misc.lready), 0);
        const int h = lane & 1, peer = lane >> 2;
        float m = misc.mred[0][h], l = misc.lred[0][h];
#pragma unroll
        for (int w = 1; w < NCW; w++) { m = fmaxf(m, misc.mred[w][h]); l += misc.lred[w][h]; }
        float x = (lane & 2) ? l : m;
        if (peer < NSPLIT && peer != split) {
            st_relaxed(&g_ml[bh][peer][split][lane & 3], x, 1);
            unsigned long long* p = &g_ml[bh][split][peer][lane & 3];
            unsigned long long v = ld_acquire(p);
            uint32_t it = 0;
            while ((v >> 32) == 0) {
                __nanosleep(500);
                v = ld_acquire(p);
                if (++it > SPIN_LIMIT) __trap();
            }
            x = __uint_as_float((uint32_t)v);
            st_relaxed(p, 0.f, 0);
        }
        __syncwarp();
        const float s_t = h ? st[1] : st[0];
        float mi[NSPLIT], M = s_t;
#pragma unroll
        for (int i = 0; i < NSPLIT; i++) { mi[i] = __shfl_sync(0xffffffffu, x, 4 * i + h); M = fmaxf(M, mi[i]); }
        const float et = ex2((s_t - M) * LOG2E);
        float L = et;
#pragma unroll
        for (int i = 0; i < NSPLIT; i++) L = fmaf(ex2((mi[i] - M) * LOG2E), __shfl_sync(0xffffffffu, x, 4 * i + 2 + h), L);
        const float inv = 1.0f / L;
        if (lane < 2) {
            misc.wgt[h][0] = ex2((m - M) * LOG2E) * inv;
            misc.wgt[h][1] = et * inv;
            mbar_arrive(smem_u32(&misc.wready));
        }
    } else {
        const int tid = threadIdx.x - 64;
        const int g = lane >> 2, t = lane & 3;
        uint32_t qf[8][2];
        {
            const uint32_t* qp = reinterpret_cast<const uint32_t*>(q + (2 * bh + (g & 1)) * HD) + t;
#pragma unroll
            for (int j = 0; j < 8; j++) { qf[j][0] = __ldg(qp + 8 * j); qf[j][1] = __ldg(qp + 8 * j + 4); }
        }
        const int oh = t & 1, od = 16 * warp + g + 8 * (t >> 1);
        unsigned short vt_raw;
        asm volatile("ld.global.nc.u16 %0, [%1];" : "=h"(vt_raw) : "l"(v_tree + bh * HD + od));
        named_sync(0, NTHREADS);

        int s = 0, ph = 0;
        const uint32_t pb = smem_u32(pbuf);
        float mx = -INFINITY;
        {
            const uint32_t koff = ring + warp * 4096 + ((lane >> 3) & 1) * 2048 + (lane & 7) * 128;
            const uint32_t x = (lane >> 4) ^ (lane & 7);
            uint32_t sp = pb + (warp >> 1) * 128 + (warp & 1) * 8 + oh * 64 + (g >> 1) * 16 + (2 * (t >> 1) + (g & 1)) * 2;
#pragma unroll 1
            for (int i = 0; i < NT; i++) {
                mbar_wait(full0 + 8 * s, ph);
                float c0[4] = {0.f, 0.f, 0.f, 0.f}, c1[4] = {0.f, 0.f, 0.f, 0.f};
                uint32_t a[8][4];
#pragma unroll
                for (int j = 0; j < 8; j++) ldsm4(a[j], koff + s * TB + (j >> 2) * 1024 + (((2 * (j & 3)) ^ x) << 4));
#pragma unroll
                for (int j = 0; j < 8; j += 2) {
                    mma16816(c0, a[j], qf[j][0], qf[j][1]);
                    mma16816(c1, a[j + 1], qf[j + 1][0], qf[j + 1][1]);
                }
                __syncwarp();
                if (lane == 0) mbar_arrive(empty0 + 8 * s);
                const float lo = (t & 1) ? c0[1] + c1[1] : c0[0] + c1[0];
                const float hi = (t & 1) ? c0[3] + c1[3] : c0[2] + c1[2];
                const __nv_bfloat16 sb = __float2bfloat16_rn(bf16r((t & 2) ? hi : lo) * SCALE);
                mx = fmaxf(mx, __bfloat162float(sb));
                asm volatile("st.shared.b16 [%0], %1;" ::"r"(sp), "h"(__bfloat16_as_ushort(sb)) : "memory");
                sp += TILE * 4;
                if (++s == STAGES) { s = 0; ph ^= 1; }
            }
        }
#pragma unroll
        for (int o = 2; o < 32; o <<= 1) mx = fmaxf(mx, __shfl_xor_sync(0xffffffffu, mx, o));
        if (lane < 2) misc.mred[warp][lane] = mx;
        named_sync(1, NCW * 32);
        {
            const int h = (tid >> 2) & 1;
            float m = misc.mred[0][h];
#pragma unroll
            for (int w = 1; w < NCW; w++) m = fmaxf(m, misc.mred[w][h]);
            float l = 0.f;
#pragma unroll
            for (int r = 0; r < KEYS * 4 / 16 / (NCW * 32); r++) {
                uint4* pp = reinterpret_cast<uint4*>(pbuf) + tid + r * NCW * 32;
                uint4 v = *pp;
                uint32_t* u = reinterpret_cast<uint32_t*>(&v);
#pragma unroll
                for (int e = 0; e < 4; e++) {
                    const float p0 = ex2((bf_lo(u[e]) - m) * LOG2E), p1 = ex2((bf_hi(u[e]) - m) * LOG2E);
                    l += p0 + p1;
                    u[e] = pack_bf16(p0, p1);
                }
                *pp = v;
            }
            l += __shfl_xor_sync(0xffffffffu, l, 1);
            l += __shfl_xor_sync(0xffffffffu, l, 2);
            l += __shfl_xor_sync(0xffffffffu, l, 8);
            l += __shfl_xor_sync(0xffffffffu, l, 16);
            if ((lane & ~4) == 0) misc.lred[warp][lane >> 2] = l;
        }
        named_sync(1, NCW * 32);
        if (tid == 0) mbar_arrive(smem_u32(&misc.lready));

        float o0[4] = {0.f, 0.f, 0.f, 0.f}, o1[4] = {0.f, 0.f, 0.f, 0.f};
        const uint32_t voff = ring + (lane >> 4) * 2048 + (warp >> 2) * 1024 + (lane & 7) * 128 +
                              ((((2 * warp + ((lane >> 3) & 1)) & 7) ^ (lane & 7)) << 4);
        const uint32_t pbase = pb + (g & 1) * 64 + t * 16;
        uint32_t poff = rotv * (TILE * 4);
        __nv_bfloat16* optr = out + (2 * bh + oh) * HD + od;
        auto load_p = [&](uint4& pf, uint32_t off) {
            asm volatile("ld.shared.v4.u32 {%0,%1,%2,%3}, [%4];" : "=r"(pf.x), "=r"(pf.y), "=r"(pf.z), "=r"(pf.w) : "r"(pbase + off));
        };
        auto pv = [&](auto nk) {
            constexpr int NK = decltype(nk)::value;
            uint4 pf[NK];
#pragma unroll
            for (int kp = 0; kp < NK; kp++) load_p(pf[kp], poff + kp * 128);
            poff = (poff + NK * 128) % (KEYS * 4);
            mbar_wait(full0 + 8 * s, ph);
            uint32_t a[2 * NK][4];
#pragma unroll
            for (int kg = 0; kg < 2 * NK; kg++) ldsm4t(a[kg], voff + s * TB + kg * 4096);
#pragma unroll
            for (int kp = 0; kp < NK; kp++) {
                mma16816(o0, a[2 * kp], pf[kp].x, pf[kp].y);
                mma16816(o1, a[2 * kp + 1], pf[kp].z, pf[kp].w);
            }
            __syncwarp();
            if (lane == 0) mbar_arrive(empty0 + 8 * s);
            if (++s == STAGES) { s = 0; ph ^= 1; }
        };
#pragma unroll 1
        for (int i = 0; i < NF; i++) pv(IC<4>{});
#pragma unroll 1
        for (int i = 0; i < NHE - 1; i++) pv(IC<2>{});
        uint4 pf0, pf1;
        load_p(pf0, poff);
        load_p(pf1, poff + 128);
        mbar_wait(smem_u32(&misc.wready), 0);
        const float2 ww = *reinterpret_cast<const float2*>(&misc.wgt[oh][0]);
        const float vt = split == 0 ? __bfloat162float(__ushort_as_bfloat16(vt_raw)) * ww.y : 0.f;
        {
            constexpr int SL = (NE - 1) % STAGES;
            mbar_wait(full0 + 8 * SL, ((NE - 1) / STAGES) & 1);
            uint32_t a[4][4];
#pragma unroll
            for (int kg = 0; kg < 4; kg++) ldsm4t(a[kg], voff + SL * TB + kg * 4096);
            mma16816(o0, a[0], pf0.x, pf0.y);
            mma16816(o1, a[1], pf0.z, pf0.w);
            mma16816(o0, a[2], pf1.x, pf1.y);
            mma16816(o1, a[3], pf1.z, pf1.w);
        }
        const float lo = (t & 1) ? o0[1] + o1[1] : o0[0] + o1[0];
        const float hi = (t & 1) ? o0[3] + o1[3] : o0[2] + o1[2];
        const float own = fmaf(ww.x, (t & 2) ? hi : lo, vt);
        const float nb = __shfl_xor_sync(0xffffffffu, own, 4);
        if (!(g & 1)) asm volatile("red.relaxed.gpu.global.add.noftz.bf16x2 [%0], %1;" ::"l"(optr), "r"(pack_bf16(own, nb)) : "memory");
    }
}

typedef CUresult (*EncodeFn)(CUtensorMap*, CUtensorMapDataType, cuuint32_t, void*, const cuuint64_t*, const cuuint64_t*,
                             const cuuint32_t*, const cuuint32_t*, CUtensorMapInterleave, CUtensorMapSwizzle,
                             CUtensorMapL2promotion, CUtensorMapFloatOOBfill);

static void make_map(CUtensorMap* m, const void* base, int rows) {
    static EncodeFn enc = nullptr;
    if (!enc) {
        cudaDriverEntryPointQueryResult qr;
        cudaGetDriverEntryPoint("cuTensorMapEncodeTiled", (void**)&enc, cudaEnableDefault, &qr);
    }
    cuuint64_t gd[4] = {64, 8, 2, (cuuint64_t)NHEAD * CTX / 8};
    cuuint64_t gs[3] = {256, 128, 2048};
    cuuint32_t bd[4] = {64, 8, 2, (cuuint32_t)rows / 8};
    cuuint32_t es[4] = {1, 1, 1, 1};
    enc(m, CU_TENSOR_MAP_DATA_TYPE_BFLOAT16, 4, const_cast<void*>(base), gd, gs, bd, es, CU_TENSOR_MAP_INTERLEAVE_NONE,
        CU_TENSOR_MAP_SWIZZLE_128B, CU_TENSOR_MAP_L2_PROMOTION_L2_128B, CU_TENSOR_MAP_FLOAT_OOB_FILL_NONE);
}

}

extern "C" void kernel_launch(void* const* d_in, const int* in_sizes, int n_in, void* d_out, int out_size) {
    (void)in_sizes; (void)n_in; (void)out_size;
    using namespace ta;
    cudaFuncSetAttribute(tree_attn_kernel, cudaFuncAttributeMaxDynamicSharedMemorySize, SMEM_BYTES);
    CUtensorMap mk, mv, mvh;
    make_map(&mk, d_in[1], TILE);
    make_map(&mv, d_in[2], TILE);
    make_map(&mvh, d_in[2], TILE / 2);
    tree_attn_kernel<<<NHEAD * NSPLIT, NTHREADS, SMEM_BYTES, cudaStreamPerThread>>>(
        (const __nv_bfloat16*)d_in[1], (const __nv_bfloat16*)d_in[0], (const __nv_bfloat16*)d_in[3],
        (const __nv_bfloat16*)d_in[4], (const __nv_bfloat16*)d_in[5], (__nv_bfloat16*)d_out, mk, mv, mvh);
}
```
